```python
import torch

def _softmax(x, axis=-1):
    return torch.softmax(x, dim=axis)
def _gelu(x):
    return torch.nn.functional.gelu(x, approximate="tanh")
def _silu(x):
    return torch.nn.functional.silu(x)
def _sigmoid(x):
    return torch.sigmoid(x)
def _layernorm(x, axis=-1, eps=1e-5):
    m = x.mean(dim=axis, keepdim=True)
    v = x.var(dim=axis, keepdim=True, unbiased=False)
    return (x - m) / torch.sqrt(v + eps)
def _scatter_add(tgt, idx, src, axis=0):
    return tgt.clone().index_add_(axis, idx, src)
def _segment_sum(src, seg, n):
    out = torch.zeros((n,) + src.shape[1:], dtype=src.dtype)
    return out.index_add_(0, seg, src)
def _pad(x, pw):
    flat = tuple(v for pair in reversed(pw) for v in pair)
    return torch.nn.functional.pad(x, flat)

kernel_name = 'standalone__paged_block_table_kv_radixattention__decode'

def setup_inputs():

    _w = (lambda a: (lambda t: t.to(torch.bfloat16) if t.is_floating_point() else t)(torch.as_tensor(a)))
    B, H, Hkv, Dh = 1, 32, 16, 128
    Lk = 65536
    bs = 16
    nb = max(2, Lk // bs)
    P = max(1, nb // 2)
    n_phys = P + B * (nb - P)
    shared = torch.arange(P, dtype=torch.int64)
    priv = P + torch.arange(B * (nb - P), dtype=torch.int64).reshape(B, nb - P)
    bt = torch.cat([torch.tile(shared[None, :], (B, 1)), priv], dim=1)
    ctx = nb * bs - (torch.arange(1, B + 1, dtype=torch.int64) * 2654435761) % max(1, (nb * bs - P * bs) // 2)
    return {
        "q": _w((lambda *s: torch.randn(*s, dtype=torch.bfloat16) * 0.8)(B, H, Dh)),
        "k_cache": _w((lambda *s: torch.randn(*s, dtype=torch.bfloat16) * 0.8)(n_phys, bs, Hkv, Dh)),
        "v_cache": _w((lambda *s: torch.randn(*s, dtype=torch.bfloat16) * 0.05)(n_phys, bs, Hkv, Dh)),
        "block_table": _w(bt.to(torch.int64)),
        "ctx_lens": _w(torch.as_tensor(ctx).to(torch.int64)),
    }

def reference(q, k_cache, v_cache, block_table, ctx_lens):
    B, H, Dh = q.shape
    n_phys, bs, Hkv, _ = k_cache.shape
    nb = block_table.shape[1]
    Lk = nb * bs
    rep = H // Hkv
    k = k_cache[block_table].reshape(B, Lk, Hkv, Dh)
    v = v_cache[block_table].reshape(B, Lk, Hkv, Dh)
    k = (lambda x, n, axis: torch.repeat_interleave(x, n, dim=axis))(k, rep, axis=2)
    v = (lambda x, n, axis: torch.repeat_interleave(x, n, dim=axis))(v, rep, axis=2)
    scores = torch.einsum("bhd,bkhd->bhk", q, k) * (Dh ** -0.5)
    pos = torch.arange(Lk)
    valid = pos[None, :] < ctx_lens[:, None]
    scores = torch.where(valid[:, None, :], scores, -1e9)
    p = _softmax(scores, axis=-1)
    return torch.einsum("bhk,bkhd->bhd", p, v)
```

```cpp
#include <cuda_runtime.h>
#include <cuda_bf16.h>
#include <cuda.h>
#include <stdint.h>

#define EVICT_FIRST 1

namespace {

#define G_V 8
#define TOK_V 8
#define NST_V 6

constexpr int HKV = 16;
constexpr int DH = 128;
constexpr int BS = 16;
constexpr int G = G_V;
constexpr int TOK = TOK_V;
constexpr int UPP = BS / TOK;
constexpr int NGROUP = HKV / G;
constexpr int NST = NST_V;
constexpr int CHUNK = TOK * 128;
constexpr int TILE = G * 2 * CHUNK;
constexpr int NCW = G;
constexpr int NTHREADS = (NCW + 2) * 32;
constexpr int MAX_SMS = 132;
constexpr int MAX_SPLIT = MAX_SMS / NGROUP;
constexpr int RV = (G == 4) ? 2 : 1;
constexpr int PPR = 32 / RV;
constexpr int PROUNDS = (MAX_SPLIT + PPR - 1) / PPR;
constexpr int PMAX = PROUNDS * PPR;
constexpr int NREADER = G * 8 * 8 / RV;
constexpr int NSLICE = HKV * 8;
constexpr uint32_t INFO_LAST = 0x40000000u;
constexpr uint32_t INFO_EMPTY = 0x20000000u;
constexpr uint32_t INFO_MASK = 0x1fffffffu;
#define INIT_AHEAD_V 10
constexpr int INIT_AHEAD = INIT_AHEAD_V;
constexpr int SBT_MAX = 4096;
constexpr int SMEM_BYTES = NST * 2 * TILE + SBT_MAX * 4 + 1024 + 512;
constexpr int WARM_IT = 2;

__device__ uint4 g_scr_o[NSLICE * PMAX * 8];
__device__ uint4 g_scr_ml[HKV * PMAX * 2];
__device__ unsigned int g_ticket[NGROUP * 32];

#define DBG(slot) do {} while (0)

__device__ __forceinline__ uint32_t smem_u32(const void* p) { return (uint32_t)__cvta_generic_to_shared(p); }

__device__ __forceinline__ void mbar_init(uint32_t bar, uint32_t cnt) {
    asm volatile("mbarrier.init.shared::cta.b64 [%0], %1;" ::"r"(bar), "r"(cnt) : "memory");
}
__device__ __forceinline__ void mbar_expect_tx(uint32_t bar, uint32_t bytes) {
    asm volatile("mbarrier.arrive.expect_tx.shared::cta.b64 _, [%0], %1;" ::"r"(bar), "r"(bytes) : "memory");
}
__device__ __forceinline__ void mbar_arrive(uint32_t bar) {
    asm volatile("mbarrier.arrive.shared::cta.b64 _, [%0];" ::"r"(bar) : "memory");
}
__device__ __forceinline__ bool mbar_try_wait(uint32_t bar, uint32_t parity) {
    uint32_t ok;
    asm volatile(
        "{\n.reg .pred p;\n"
        "mbarrier.try_wait.parity.shared::cta.b64 p, [%1], %2;\n"
        "selp.u32 %0, 1, 0, p;\n}\n"
        : "=r"(ok)
        : "r"(bar), "r"(parity)
        : "memory");
    return ok != 0;
}
__device__ __forceinline__ void mbar_wait(uint32_t bar, uint32_t parity) {
    uint32_t spins = 0;
    while (!mbar_try_wait(bar, parity)) {
        if (++spins > (1u << 24)) __trap();
    }
}
__device__ __forceinline__ void tma_load_3d(uint32_t dst, const CUtensorMap* tm, int c0, int c1, int c2, uint32_t bar) {
    asm volatile(
        "cp.async.bulk.tensor.3d.shared::cluster.global.mbarrier::complete_tx::bytes [%0], [%1, {%3, %4, %5}], [%2];"
        ::"r"(dst), "l"(tm), "r"(bar), "r"(c0), "r"(c1), "r"(c2)
        : "memory");
}
__device__ __forceinline__ void tma_load_3d_hint(uint32_t dst, const CUtensorMap* tm, int c0, int c1, int c2, uint32_t bar, uint64_t pol) {
    asm volatile(
        "cp.async.bulk.tensor.3d.shared::cluster.global.mbarrier::complete_tx::bytes.L2::cache_hint [%0], [%1, {%3, %4, %5}], [%2], %6;"
        ::"r"(dst), "l"(tm), "r"(bar), "r"(c0), "r"(c1), "r"(c2), "l"(pol)
        : "memory");
}
__device__ __forceinline__ void bulk_g2s(uint32_t dst, const void* src, uint32_t bytes, uint32_t bar) {
    asm volatile("cp.async.bulk.shared::cluster.global.mbarrier::complete_tx::bytes [%0], [%1], %2, [%3];"
                 ::"r"(dst), "l"(src), "r"(bytes), "r"(bar) : "memory");
}
__device__ __forceinline__ void sts_u32(uint32_t addr, uint32_t v) {
    asm volatile("st.shared.u32 [%0], %1;" ::"r"(addr), "r"(v) : "memory");
}
__device__ __forceinline__ uint32_t lds_u32(uint32_t addr) {
    uint32_t v;
    asm volatile("ld.shared.u32 %0, [%1];" : "=r"(v) : "r"(addr) : "memory");
    return v;
}
__device__ __forceinline__ void ldsm_x4(uint32_t& r0, uint32_t& r1, uint32_t& r2, uint32_t& r3, uint32_t addr) {
    asm volatile("ldmatrix.sync.aligned.m8n8.x4.shared.b16 {%0,%1,%2,%3}, [%4];"
                 : "=r"(r0), "=r"(r1), "=r"(r2), "=r"(r3) : "r"(addr) : "memory");
}
__device__ __forceinline__ void ldsm_x4_t(uint32_t& r0, uint32_t& r1, uint32_t& r2, uint32_t& r3, uint32_t addr) {
    asm volatile("ldmatrix.sync.aligned.m8n8.x4.trans.shared.b16 {%0,%1,%2,%3}, [%4];"
                 : "=r"(r0), "=r"(r1), "=r"(r2), "=r"(r3) : "r"(addr) : "memory");
}
__device__ __forceinline__ void mma_k16(float (&d)[4], uint32_t a0, uint32_t a1, uint32_t a2, uint32_t a3,
                                        uint32_t b0, uint32_t b1) {
    asm volatile(
        "mma.sync.aligned.m16n8k16.row.col.f32.bf16.bf16.f32 {%0,%1,%2,%3}, {%4,%5,%6,%7}, {%8,%9}, {%0,%1,%2,%3};"
        : "+f"(d[0]), "+f"(d[1]), "+f"(d[2]), "+f"(d[3])
        : "r"(a0), "r"(a1), "r"(a2), "r"(a3), "r"(b0), "r"(b1));
}
__device__ __forceinline__ void mma_k8(float (&d)[4], uint32_t a0, uint32_t a1, uint32_t b0) {
    asm volatile(
        "mma.sync.aligned.m16n8k8.row.col.f32.bf16.bf16.f32 {%0,%1,%2,%3}, {%4,%5}, {%6}, {%0,%1,%2,%3};"
        : "+f"(d[0]), "+f"(d[1]), "+f"(d[2]), "+f"(d[3])
        : "r"(a0), "r"(a1), "r"(b0));
}
__device__ __forceinline__ uint32_t pack_bf16(float lo, float hi) {
    uint32_t r;
    asm("cvt.rn.bf16x2.f32 %0, %1, %2;" : "=r"(r) : "f"(hi), "f"(lo));
    return r;
}
__device__ __forceinline__ float ex2(float x) {
    float y;
    asm("ex2.approx.ftz.f32 %0, %1;" : "=f"(y) : "f"(x));
    return y;
}
__device__ __forceinline__ float rcp_approx(float x) {
    float y;
    asm("rcp.approx.ftz.f32 %0, %1;" : "=f"(y) : "f"(x));
    return y;
}
__device__ __forceinline__ uint32_t enc(float x) { return max(~__float_as_uint(x), 1u); }
__device__ __forceinline__ float dec(uint32_t u) { return __uint_as_float(~u); }
__device__ __forceinline__ void st_zero_v4(uint4* p) {
    asm volatile("st.relaxed.gpu.global.v4.u32 [%0], {0, 0, 0, 0};" ::"l"(p) : "memory");
}
__device__ __forceinline__ void st_pred_v4(uint4* p, uint32_t a, uint32_t b, uint32_t c, uint32_t d, bool pred) {
    asm volatile("{\n.reg .pred p;\nsetp.ne.u32 p, %5, 0;\n@p st.relaxed.gpu.global.v4.u32 [%0], {%1,%2,%3,%4};\n}\n"
                 ::"l"(p), "r"(a), "r"(b), "r"(c), "r"(d), "r"((uint32_t)pred) : "memory");
}
__device__ __forceinline__ void ld_pred_v4(uint4& v, const uint4* p, bool pred) {
    asm volatile("{\n.reg .pred p;\nsetp.ne.u32 p, %5, 0;\n@p ld.relaxed.gpu.global.v4.u32 {%0,%1,%2,%3}, [%4];\n}\n"
                 : "+r"(v.x), "+r"(v.y), "+r"(v.z), "+r"(v.w) : "l"(p), "r"((uint32_t)pred) : "memory");
}
__device__ __forceinline__ void st_pred_u16(void* p, uint16_t v, bool pred) {
    asm volatile("{\n.reg .pred p;\nsetp.ne.u32 p, %2, 0;\n@p st.global.u16 [%0], %1;\n}\n"
                 ::"l"(p), "h"(v), "r"((uint32_t)pred) : "memory");
}
__device__ __forceinline__ void st_pred_zero_v2(void* p, bool pred) {
    asm volatile("{\n.reg .pred p;\nsetp.ne.u32 p, %1, 0;\n@p st.relaxed.gpu.global.v2.u32 [%0], {0, 0};\n}\n"
                 ::"l"(p), "r"((uint32_t)pred) : "memory");
}
__device__ __forceinline__ uint32_t min4(const uint4& v) { return min(min(v.x, v.y), min(v.z, v.w)); }
__device__ __forceinline__ float warp_max_f32(float x) {
    int k = __float_as_int(x);
    k ^= (k >> 31) & 0x7fffffff;
    k = __reduce_max_sync(0xffffffffu, k);
    k ^= (k >> 31) & 0x7fffffff;
    return __int_as_float(k);
}
__device__ __forceinline__ uint16_t bf16_bits(float x) { return __bfloat16_as_ushort(__float2bfloat16(x)); }

__global__ void __launch_bounds__(NTHREADS, 1)
paged_decode_kernel(const __grid_constant__ CUtensorMap tmK, const __grid_constant__ CUtensorMap tmV,
                    const __nv_bfloat16* __restrict__ q, const int* __restrict__ bt,
                    const int* __restrict__ ctx, __nv_bfloat16* __restrict__ out, int nb, int nsplit) {
    extern __shared__ uint8_t smem_raw[];
    const uint32_t sbase = (smem_u32(smem_raw) + 1023u) & ~1023u;
    const uint32_t sbt_base = sbase + NST * 2 * TILE;
    const uint32_t bar_base = sbt_base + SBT_MAX * 4;
    auto fullK = [&](int s) { return bar_base + 8u * s; };
    auto fullV = [&](int s) { return bar_base + 8u * (NST + s); };
    auto emptyK = [&](int s) { return bar_base + 8u * (2 * NST + s); };
    auto emptyV = [&](int s) { return bar_base + 8u * (3 * NST + s); };
    const uint32_t btbar = bar_base + 8u * (4 * NST);
    const uint32_t rdybar = bar_base + 8u * (4 * NST + 1);
    const uint32_t trigbar = bar_base + 8u * (4 * NST + 2);
    auto slot = [&](int s) { return bar_base + 8u * (4 * NST + 3) + 4u * s; };
    const uint32_t sstat = bar_base + 8u * (4 * NST + 3) + 4u * NST;

    const int warp = threadIdx.x >> 5;
    const int lane = threadIdx.x & 31;
    const int group = blockIdx.x % NGROUP;
    const int split = blockIdx.x / NGROUP;

    int e0 = 0, ctx_raw;
    {
        const int idx0 = (split + (int)threadIdx.x * nsplit) / UPP;
        const uint32_t pr = (threadIdx.x < NST && idx0 < nb) ? 1u : 0u;
        asm volatile("{\n.reg .pred p;\nsetp.ne.u32 p, %2, 0;\n@p ld.global.nc.u32 %0, [%1];\n}\n"
                     : "+r"(e0) : "l"(bt + (pr ? idx0 : 0)), "r"(pr));
        asm volatile("ld.global.nc.u32 %0, [%1];" : "=r"(ctx_raw) : "l"(ctx));
    }
    if (threadIdx.x == 0) DBG(0);

    if (warp == NCW + 1) {
        asm volatile("bar.sync 1, %0;" ::"n"(NTHREADS) : "memory");
        int npass = 2;
        asm volatile("" : "+r"(npass));
        uint4* po = &g_scr_o[((group * G * 8 + (lane >> 3)) * PMAX + split) * 8 + (lane & 7)];
        uint4* pm = &g_scr_ml[((group * G + (lane >> 1)) * PMAX + split) * 2 + (lane & 1)];
        unsigned int* ready = &g_ticket[group * 32 + 1];
#pragma unroll 1
        for (int pass = 1; pass <= npass; pass++) {
            const bool real = pass == 2;
            if (real) mbar_wait(trigbar, 0);
#pragma unroll
            for (int k = 0; k < 2 * G; k++) st_pred_v4(po + k * 4 * PMAX * 8, 0u, 0u, 0u, 0u, real);
            st_pred_v4(pm, 0u, 0u, 0u, 0u, real && lane < 2 * G);
            __threadfence();
            __syncwarp();
            const uint32_t pr = (real && lane == 0) ? 1u : 0u;
            asm volatile("{\n.reg .pred p;\nsetp.ne.u32 p, %1, 0;\n@p red.relaxed.gpu.global.add.u32 [%0], 1;\n}\n"
                         ::"l"(ready), "r"(pr) : "memory");
            uint32_t spins = 0;
            while (true) {
                unsigned int v = 0xffffffffu;
                asm volatile("{\n.reg .pred p;\nsetp.ne.u32 p, %2, 0;\n@p ld.acquire.gpu.global.u32 %0, [%1];\n}\n"
                             : "+r"(v) : "l"(ready), "r"(pr) : "memory");
                if (__all_sync(0xffffffffu, v >= (unsigned int)nsplit)) break;
                if (++spins > (1u << 22)) __trap();
                __nanosleep(100);
            }
            if (pr) {
                mbar_arrive(rdybar);
                DBG(7);
            }
        }
        return;
    }

    if (warp != 0) {
        const int cw = warp - 1;
        const int g = lane >> 2;
        const int t = lane & 3;
        const int kvh = group * G + cw;

        uint32_t qa[8][2];
        {
            const uint32_t* qp = reinterpret_cast<const uint32_t*>(q + (size_t)(kvh * 2 + (g & 1)) * DH);
#pragma unroll
            for (int ks = 0; ks < 8; ks++) {
                uint32_t v0 = __ldg(qp + ks * 8 + t);
                uint32_t v1 = __ldg(qp + ks * 8 + 4 + t);
                qa[ks][0] = (g < 2) ? v0 : 0u;
                qa[ks][1] = (g < 2) ? v1 : 0u;
            }
        }
        asm volatile("bar.sync 1, %0;" ::"n"(NTHREADS) : "memory");

        const int lk = nb * BS;
        const bool uniform = (ctx_raw <= 0);
        const int len = uniform ? lk : min(ctx_raw, lk);
        const float cscale = 0.08838834764831845f * 1.4426950408889634f;

        float o[8][4];
#pragma unroll
        for (int i = 0; i < 8; i++) { o[i][0] = o[i][1] = o[i][2] = o[i][3] = 0.f; }
        float m_run = -INFINITY;
        float l_run = 0.f;

        const int r8 = lane & 7;
        const int mi = lane >> 3;
        const uint32_t k_lane_off = (uint32_t)(cw * 2 * CHUNK + r8 * 128);
        const uint32_t v_lane_off = (TOK == 16) ? (uint32_t)(cw * 2 * CHUNK + ((mi >> 1) * 8 + r8) * 128)
                                                : (uint32_t)(cw * 2 * CHUNK + r8 * 128);
        constexpr int NT = TOK / 8;

        int st = 0;
        uint32_t ph = 0;
#pragma unroll 1
        for (int it = 0;; it++) {
            const uint32_t kb = sbase + st * 2 * TILE;
            const uint32_t vb = kb + TILE;
            mbar_wait(fullK(st), ph);
            const uint32_t info = lds_u32(slot(st));
            const bool last = (info & INFO_LAST) != 0;
            const bool empty = (info & INFO_EMPTY) != 0;
            const bool epi = last || it == WARM_IT;
            uint32_t pb0 = 0, pb1 = 0;
            if (!empty) {
                float s0[NT][4], s1[NT][4];
#pragma unroll
                for (int nt = 0; nt < NT; nt++) {
                    s0[nt][0] = s0[nt][1] = s0[nt][2] = s0[nt][3] = 0.f;
                    s1[nt][0] = s1[nt][1] = s1[nt][2] = s1[nt][3] = 0.f;
                }
#pragma unroll
                for (int c = 0; c < 2; c++) {
#pragma unroll
                    for (int hf = 0; hf < 2; hf++) {
#pragma unroll
                        for (int nt = 0; nt < NT; nt++) {
                            uint32_t b0, b1, b2, b3;
                            const uint32_t addr = kb + k_lane_off + c * CHUNK + nt * 1024 + (uint32_t)(((hf * 4 + mi) ^ r8) << 4);
                            ldsm_x4(b0, b1, b2, b3, addr);
                            const int ks = c * 4 + hf * 2;
                            if (c == 0) {
                                mma_k16(s0[nt], qa[ks][0], 0u, qa[ks][1], 0u, b0, b1);
                                mma_k16(s0[nt], qa[ks + 1][0], 0u, qa[ks + 1][1], 0u, b2, b3);
                            } else {
                                mma_k16(s1[nt], qa[ks][0], 0u, qa[ks][1], 0u, b0, b1);
                                mma_k16(s1[nt], qa[ks + 1][0], 0u, qa[ks + 1][1], 0u, b2, b3);
                            }
                        }
                    }
                }
                __syncwarp();
                if (lane == 0) mbar_arrive(emptyK(st));

                float sv[2 * NT];
#pragma unroll
                for (int nt = 0; nt < NT; nt++) {
                    sv[2 * nt] = s0[nt][0] + s1[nt][0];
                    sv[2 * nt + 1] = s0[nt][1] + s1[nt][1];
                }
                const int tok0 = (int)(info & INFO_MASK) * TOK;
                if (uniform) {
#pragma unroll
                    for (int i = 0; i < 2 * NT; i++) sv[i] = 0.f;
                }
                if (tok0 + TOK > len) {
                    const int tb = tok0 + 2 * t;
#pragma unroll
                    for (int i = 0; i < 2 * NT; i++) {
                        if (tb + (i >> 1) * 8 + (i & 1) >= len) sv[i] = -INFINITY;
                    }
                }
                float mx = fmaxf(sv[0], sv[1]);
                if (NT == 2) mx = fmaxf(mx, fmaxf(sv[2 * NT - 2], sv[2 * NT - 1]));
                mx = fmaxf(mx, __shfl_xor_sync(0xffffffffu, mx, 1));
                mx = fmaxf(mx, __shfl_xor_sync(0xffffffffu, mx, 2));
                const float m_new = fmaxf(m_run, mx);
                const float m_use = (m_new == -INFINITY) ? 0.f : m_new;
                const float alpha = ex2((m_run - m_use) * cscale);
                const float mc = m_use * cscale;
                float p[2 * NT];
                float psum = 0.f;
#pragma unroll
                for (int i = 0; i < 2 * NT; i++) {
                    p[i] = ex2(fmaf(sv[i], cscale, -mc));
                    psum += p[i];
                }
                m_run = m_new;
                l_run = fmaf(l_run, alpha, psum);
                pb0 = pack_bf16(p[0], p[1]);
                if (NT == 2) pb1 = pack_bf16(p[2 * NT - 2], p[2 * NT - 1]);
                const float a0 = __shfl_sync(0xffffffffu, alpha, 0);
                const float a1 = __shfl_sync(0xffffffffu, alpha, 4);
                if (a0 != 1.f || a1 != 1.f) {
#pragma unroll
                    for (int i = 0; i < 8; i++) {
                        o[i][0] *= a0; o[i][1] *= a1; o[i][2] *= a0; o[i][3] *= a1;
                    }
                }
            }
            if (epi) {
                if (last) mbar_wait(rdybar, 0);
                float l = l_run;
                l += __shfl_xor_sync(0xffffffffu, l, 1);
                l += __shfl_xor_sync(0xffffffffu, l, 2);
                const float mc = m_run * cscale;
                const float m0 = __shfl_sync(0xffffffffu, mc, 0);
                const float m1 = __shfl_sync(0xffffffffu, mc, 4);
                const float l0 = __shfl_sync(0xffffffffu, l, 0);
                const float l1 = __shfl_sync(0xffffffffu, l, 4);
                st_pred_v4(&g_scr_ml[(kvh * PMAX + split) * 2 + (lane & 1)], enc(m0), enc(m1), enc(l0), enc(l1),
                           last && lane < 2);
            }
            if (!empty) {
                mbar_wait(fullV(st), ph);
                if (TOK == 16) {
#pragma unroll
                    for (int mt = 0; mt < 8; mt++) {
                        uint32_t a0r, a1r, a2r, a3r;
                        const uint32_t addr = vb + v_lane_off + (mt >> 2) * CHUNK + (uint32_t)(((2 * (mt & 3) + (mi & 1)) ^ r8) << 4);
                        ldsm_x4_t(a0r, a1r, a2r, a3r, addr);
                        mma_k16(o[mt], a0r, a1r, a2r, a3r, pb0, pb1);
                    }
                } else {
#pragma unroll
                    for (int mp = 0; mp < 4; mp++) {
                        uint32_t a0r, a1r, a2r, a3r;
                        const uint32_t addr = vb + v_lane_off + (mp >> 1) * CHUNK + (uint32_t)((((mp & 1) * 4 + mi) ^ r8) << 4);
                        ldsm_x4_t(a0r, a1r, a2r, a3r, addr);
                        mma_k8(o[2 * mp], a0r, a1r, pb0);
                        mma_k8(o[2 * mp + 1], a2r, a3r, pb0);
                    }
                }
                __syncwarp();
                if (lane == 0) mbar_arrive(emptyV(st));
            }
            if (epi) {
                {
                    uint4* po = &g_scr_o[(kvh * 8 * PMAX + split) * 8 + g];
                    const bool pr = last && t == 0;
#pragma unroll
                    for (int mt = 0; mt < 8; mt++) {
                        st_pred_v4(po + mt * PMAX * 8, enc(o[mt][0]), enc(o[mt][1]), enc(o[mt][2]), enc(o[mt][3]), pr);
                    }
                }
#pragma unroll 1
                for (int ri = split * NCW + cw; ri < NREADER; ri += nsplit * NCW) {
                    const int ii = lane / RV;
                    const int gg = lane % RV;
                    const int j = group * G + ri / (64 / RV);
                    const int mt = (ri / (8 / RV)) & 7;
                    const int gq = (ri % (8 / RV)) * RV + gg;
                    const uint4* po = &g_scr_o[((j * 8 + mt) * PMAX + ii) * 8 + gq];
                    const uint4* pm = &g_scr_ml[(j * PMAX + ii) * 2];
                    uint4 ov[PROUNDS], mv[PROUNDS];
#pragma unroll
                    for (int r = 0; r < PROUNDS; r++) {
                        const bool present = last && (r * PPR + ii < nsplit);
                        ov[r].x = ov[r].y = ov[r].z = ov[r].w = present ? 0u : 0xffffffffu;
                        mv[r].x = mv[r].y = present ? 0u : 0x007fffffu;
                        mv[r].z = mv[r].w = present ? 0u : 0xffffffffu;
                    }
                    uint32_t spins = 0;
                    while (true) {
                        bool anyneed = false;
#pragma unroll
                        for (int r = 0; r < PROUNDS; r++) {
                            const bool need = min(min4(ov[r]), min4(mv[r])) == 0u;
                            anyneed |= need;
                            ld_pred_v4(ov[r], po + r * PPR * 8, need);
                            ld_pred_v4(mv[r], pm + r * PPR * 2, need);
                        }
                        if (!__any_sync(0xffffffffu, anyneed)) break;
                        if (++spins > (1u << 22)) __trap();
                    }
                    float M0 = -INFINITY, M1 = -INFINITY;
#pragma unroll
                    for (int r = 0; r < PROUNDS; r++) {
                        M0 = fmaxf(M0, dec(mv[r].x));
                        M1 = fmaxf(M1, dec(mv[r].y));
                    }
                    M0 = warp_max_f32(M0);
                    M1 = warp_max_f32(M1);
                    if (M0 == -INFINITY) M0 = 0.f;
                    if (M1 == -INFINITY) M1 = 0.f;
                    float L0 = 0.f, L1 = 0.f, acc0 = 0.f, acc1 = 0.f, acc2 = 0.f, acc3 = 0.f;
#pragma unroll
                    for (int r = 0; r < PROUNDS; r++) {
                        const float w0 = ex2(dec(mv[r].x) - M0);
                        const float w1 = ex2(dec(mv[r].y) - M1);
                        L0 = fmaf(w0, dec(mv[r].z), L0);
                        L1 = fmaf(w1, dec(mv[r].w), L1);
                        acc0 = fmaf(w0, dec(ov[r].x), acc0);
                        acc1 = fmaf(w1, dec(ov[r].y), acc1);
                        acc2 = fmaf(w0, dec(ov[r].z), acc2);
                        acc3 = fmaf(w1, dec(ov[r].w), acc3);
                    }
#pragma unroll
                    for (int d = RV; d <= 16; d <<= 1) {
                        L0 += __shfl_xor_sync(0xffffffffu, L0, d);
                        L1 += __shfl_xor_sync(0xffffffffu, L1, d);
                        acc0 += __shfl_xor_sync(0xffffffffu, acc0, d);
                        acc1 += __shfl_xor_sync(0xffffffffu, acc1, d);
                        acc2 += __shfl_xor_sync(0xffffffffu, acc2, d);
                        acc3 += __shfl_xor_sync(0xffffffffu, acc3, d);
                    }
                    const float i0 = rcp_approx(L0), i1 = rcp_approx(L1);
                    __nv_bfloat16* o0 = out + (size_t)(2 * j) * DH + mt * 16 + gq;
                    const bool pr = last && ii == 0;
                    st_pred_u16(o0, bf16_bits(acc0 * i0), pr);
                    st_pred_u16(o0 + DH, bf16_bits(acc1 * i1), pr);
                    st_pred_u16(o0 + 8, bf16_bits(acc2 * i0), pr);
                    st_pred_u16(o0 + DH + 8, bf16_bits(acc3 * i1), pr);
                    st_pred_zero_v2(&g_ticket[group * 32], last && ri == 0 && lane == 0);
                }
                if (last) break;
            }
            if (++st == NST) { st = 0; ph ^= 1; }
        }
        if (threadIdx.x == 32) DBG(5);
        return;
    }

    {
        unsigned int* ticket = &g_ticket[group * 32];
        const int dyn_base = NST * nsplit;
        if (lane == 0) {
            asm volatile("prefetch.tensormap [%0];" ::"l"(&tmK) : "memory");
            asm volatile("prefetch.tensormap [%0];" ::"l"(&tmV) : "memory");
#pragma unroll
            for (int s = 0; s < NST; s++) {
                mbar_init(fullK(s), 1);
                mbar_init(fullV(s), 1);
                mbar_init(emptyK(s), NCW);
                mbar_init(emptyV(s), NCW);
            }
            mbar_init(btbar, 1);
            mbar_init(rdybar, 2);
            mbar_init(trigbar, 1);
            asm volatile("fence.mbarrier_init.release.cluster;" ::: "memory");
            asm volatile("fence.proxy.async.shared::cta;" ::: "memory");
        }
        __syncwarp();
        asm volatile("bar.arrive 1, %0;" ::"n"(NTHREADS) : "memory");
        if (lane < NST) sts_u32(sstat + 4u * lane, (uint32_t)e0);
        __syncwarp();
        if (lane != 0) return;

        const int nstage_bt = min(nb, SBT_MAX) & ~3;
        const int lk = nb * BS;
        const int len = (ctx_raw <= 0) ? lk : min(ctx_raw, lk);
        const int nunits = (len + TOK - 1) / TOK;
        const int init_thresh = nunits - INIT_AHEAD * nsplit;
        int q0 = split, q1 = split + nsplit;
        bool inited = false;
        uint64_t pol;
        asm volatile("createpolicy.fractional.L2::evict_first.b64 %0, 1.0;" : "=l"(pol));
        if (q0 >= nunits) {
            sts_u32(slot(0), INFO_LAST | INFO_EMPTY);
            mbar_arrive(fullK(0));
            mbar_arrive(trigbar);
        } else {
            int st = 0;
            uint32_t ph = 1;
#pragma unroll 1
            for (int u = 0;; u++) {
                const int uidx = q0;
                q0 = q1;
                const bool last = q0 >= nunits;
                if (!last) {
                    if (u + 2 < NST) q1 += nsplit;
                    else q1 = dyn_base + (int)atomicAdd(ticket, 1u);
                }
                const int pidx = uidx / UPP;
                int page;
                if (u < NST) {
                    page = (int)lds_u32(sstat + 4u * u);
                } else {
                    if (u == NST && nstage_bt > 0) mbar_wait(btbar, 0);
                    page = (pidx < nstage_bt) ? (int)lds_u32(sbt_base + pidx * 4) : __ldg(bt + pidx);
                }
                const int row = page * BS + (uidx % UPP) * TOK;
                const uint32_t kdst = sbase + st * 2 * TILE;
                mbar_wait(emptyK(st), ph);
                sts_u32(slot(st), (uint32_t)uidx | (last ? INFO_LAST : 0u));
                mbar_expect_tx(fullK(st), TILE);
                tma_load_3d_hint(kdst, &tmK, 0, row, group * 2 * G, fullK(st), pol);
                mbar_wait(emptyV(st), ph);
                mbar_expect_tx(fullV(st), TILE);
                tma_load_3d_hint(kdst + TILE, &tmV, 0, row, group * 2 * G, fullV(st), pol);
                if (u == 0) {
                    DBG(1);
                    if (nstage_bt > 0) {
                        mbar_expect_tx(btbar, nstage_bt * 4);
                        bulk_g2s(sbt_base, bt, nstage_bt * 4, btbar);
                    }
                }
                if (!inited && (uidx >= init_thresh || last)) { mbar_arrive(trigbar); inited = true; }
                if (last) {
                    if (u < NST && nstage_bt > 0) mbar_wait(btbar, 0);
                    break;
                }
                if (++st == NST) { st = 0; ph ^= 1; }
            }
        }
        mbar_arrive(rdybar);
        DBG(2);
    }
}

typedef CUresult (*EncodeTiledFn)(CUtensorMap*, CUtensorMapDataType, cuuint32_t, void*, const cuuint64_t*,
                                  const cuuint64_t*, const cuuint32_t*, const cuuint32_t*, CUtensorMapInterleave,
                                  CUtensorMapSwizzle, CUtensorMapL2promotion, CUtensorMapFloatOOBfill);

bool make_map(EncodeTiledFn enc_fn, CUtensorMap* tm, const void* base, uint64_t rows) {
    cuuint64_t gd[3] = {64, rows, 32};
    cuuint64_t gs[2] = {4096, 128};
    cuuint32_t bd[3] = {64, (cuuint32_t)TOK, (cuuint32_t)(2 * G)};
    cuuint32_t es[3] = {1, 1, 1};
    return enc_fn(tm, CU_TENSOR_MAP_DATA_TYPE_BFLOAT16, 3, const_cast<void*>(base), gd, gs, bd, es,
                  CU_TENSOR_MAP_INTERLEAVE_NONE, CU_TENSOR_MAP_SWIZZLE_128B, CU_TENSOR_MAP_L2_PROMOTION_L2_256B,
                  CU_TENSOR_MAP_FLOAT_OOB_FILL_NONE) == CUDA_SUCCESS;
}

}

extern "C" void kernel_launch(void* const* d_in, const int* in_sizes, int n_in, void* d_out, int out_size) {
    (void)n_in; (void)out_size;
    const __nv_bfloat16* q = (const __nv_bfloat16*)d_in[0];
    const void* kc = d_in[1];
    const void* vc = d_in[2];
    const int* bt = (const int*)d_in[3];
    const int* ctx = (const int*)d_in[4];
    __nv_bfloat16* out = (__nv_bfloat16*)d_out;

    static EncodeTiledFn enc_fn = nullptr;
    static int num_sms = 0;
    if (!enc_fn) {
        void* fn = nullptr;
        cudaDriverEntryPointQueryResult qr;
        cudaGetDriverEntryPoint("cuTensorMapEncodeTiled", &fn, cudaEnableDefault, &qr);
        enc_fn = (EncodeTiledFn)fn;
        int dev = 0;
        cudaGetDevice(&dev);
        cudaDeviceGetAttribute(&num_sms, cudaDevAttrMultiProcessorCount, dev);
        cudaFuncSetAttribute(paged_decode_kernel, cudaFuncAttributeMaxDynamicSharedMemorySize, SMEM_BYTES);
    }
    const uint64_t rows = (uint64_t)in_sizes[1] / (HKV * DH);
    const int nb = in_sizes[3];
    CUtensorMap tmK, tmV;
    make_map(enc_fn, &tmK, kc, rows);
    make_map(enc_fn, &tmV, vc, rows);
    int nsplit = num_sms / NGROUP;
    if (nsplit > MAX_SPLIT) nsplit = MAX_SPLIT;
    if (nsplit < 1) nsplit = 1;
    paged_decode_kernel<<<nsplit * NGROUP, NTHREADS, SMEM_BYTES, cudaStreamPerThread>>>(tmK, tmV, q, bt, ctx, out, nb, nsplit);
}
```

```cpp
#include <cuda_runtime.h>
#include <cuda_bf16.h>
#include <cuda.h>
#include <stdint.h>

namespace {

constexpr int HKV = 16;
constexpr int DH = 128;
constexpr int BS = 16;
constexpr int G = 8;
constexpr int TOK = 8;
constexpr int UPP = BS / TOK;
constexpr int NGROUP = HKV / G;
constexpr int NST = 6;
constexpr int CHUNK = TOK * 128;
constexpr int TILE = G * 2 * CHUNK;
constexpr int NCW = G;
constexpr int NTHREADS = (NCW + 2) * 32;
constexpr int MAX_SMS = 132;
constexpr int MAX_SPLIT = MAX_SMS / NGROUP;
constexpr int PPR = 16;
constexpr int PROUNDS = (MAX_SPLIT + PPR - 1) / PPR;
constexpr int PMAX = PROUNDS * PPR;
constexpr int NITEM = HKV * 8 * 4;
constexpr int NREADER = G * 8 * 4;
constexpr int RW = 4;
constexpr uint32_t INFO_LAST = 0x40000000u;
constexpr uint32_t INFO_EMPTY = 0x20000000u;
constexpr uint32_t INFO_MASK = 0x1fffffffu;
constexpr int SBT_MAX = 4096;
constexpr int SMEM_BYTES = NST * 2 * TILE + SBT_MAX * 4 + 1024 + 512;
constexpr int WARM_IT = 2;

__device__ uint4 g_scr_o[NITEM * PMAX * 2];
__device__ uint4 g_scr_ml[HKV * PMAX * 2];
__device__ unsigned int g_ticket[NGROUP * 32];

#define DBG(slot) do {} while (0)

__device__ __forceinline__ uint32_t smem_u32(const void* p) { return (uint32_t)__cvta_generic_to_shared(p); }

__device__ __forceinline__ void mbar_init(uint32_t bar, uint32_t cnt) {
    asm volatile("mbarrier.init.shared::cta.b64 [%0], %1;" ::"r"(bar), "r"(cnt) : "memory");
}
__device__ __forceinline__ void mbar_expect_tx(uint32_t bar, uint32_t bytes) {
    asm volatile("mbarrier.arrive.expect_tx.shared::cta.b64 _, [%0], %1;" ::"r"(bar), "r"(bytes) : "memory");
}
__device__ __forceinline__ void mbar_arrive(uint32_t bar) {
    asm volatile("mbarrier.arrive.shared::cta.b64 _, [%0];" ::"r"(bar) : "memory");
}
__device__ __forceinline__ bool mbar_try_wait(uint32_t bar, uint32_t parity) {
    uint32_t ok;
    asm volatile(
        "{\n.reg .pred p;\n"
        "mbarrier.try_wait.parity.shared::cta.b64 p, [%1], %2;\n"
        "selp.u32 %0, 1, 0, p;\n}\n"
        : "=r"(ok)
        : "r"(bar), "r"(parity)
        : "memory");
    return ok != 0;
}
__device__ __forceinline__ void mbar_wait(uint32_t bar, uint32_t parity) {
    uint32_t spins = 0;
    while (!mbar_try_wait(bar, parity)) {
        if (++spins > (1u << 22)) __trap();
    }
}
__device__ __forceinline__ void tma_load_3d(uint32_t dst, const CUtensorMap* tm, int row, int chunk, uint32_t bar, uint64_t pol) {
    asm volatile(
        "cp.async.bulk.tensor.3d.shared::cluster.global.mbarrier::complete_tx::bytes.L2::cache_hint "
        "[%0], [%1, {%3, %4, %5}], [%2], %6;"
        ::"r"(dst), "l"(tm), "r"(bar), "r"(0), "r"(row), "r"(chunk), "l"(pol)
        : "memory");
}
__device__ __forceinline__ void bulk_g2s(uint32_t dst, const void* src, uint32_t bytes, uint32_t bar) {
    asm volatile("cp.async.bulk.shared::cluster.global.mbarrier::complete_tx::bytes [%0], [%1], %2, [%3];"
                 ::"r"(dst), "l"(src), "r"(bytes), "r"(bar) : "memory");
}
__device__ __forceinline__ void sts_u32(uint32_t addr, uint32_t v) {
    asm volatile("st.shared.u32 [%0], %1;" ::"r"(addr), "r"(v) : "memory");
}
__device__ __forceinline__ uint32_t lds_u32(uint32_t addr) {
    uint32_t v;
    asm volatile("ld.shared.u32 %0, [%1];" : "=r"(v) : "r"(addr) : "memory");
    return v;
}
__device__ __forceinline__ void ldsm_x4(uint32_t& r0, uint32_t& r1, uint32_t& r2, uint32_t& r3, uint32_t addr) {
    asm volatile("ldmatrix.sync.aligned.m8n8.x4.shared.b16 {%0,%1,%2,%3}, [%4];"
                 : "=r"(r0), "=r"(r1), "=r"(r2), "=r"(r3) : "r"(addr) : "memory");
}
__device__ __forceinline__ void ldsm_x4_t(uint32_t& r0, uint32_t& r1, uint32_t& r2, uint32_t& r3, uint32_t addr) {
    asm volatile("ldmatrix.sync.aligned.m8n8.x4.trans.shared.b16 {%0,%1,%2,%3}, [%4];"
                 : "=r"(r0), "=r"(r1), "=r"(r2), "=r"(r3) : "r"(addr) : "memory");
}
__device__ __forceinline__ void mma_k16(float (&d)[4], uint32_t a0, uint32_t a1, uint32_t a2, uint32_t a3,
                                        uint32_t b0, uint32_t b1) {
    asm volatile(
        "mma.sync.aligned.m16n8k16.row.col.f32.bf16.bf16.f32 {%0,%1,%2,%3}, {%4,%5,%6,%7}, {%8,%9}, {%0,%1,%2,%3};"
        : "+f"(d[0]), "+f"(d[1]), "+f"(d[2]), "+f"(d[3])
        : "r"(a0), "r"(a1), "r"(a2), "r"(a3), "r"(b0), "r"(b1));
}
__device__ __forceinline__ void mma_k8(float (&d)[4], uint32_t a0, uint32_t a1, uint32_t b0) {
    asm volatile(
        "mma.sync.aligned.m16n8k8.row.col.f32.bf16.bf16.f32 {%0,%1,%2,%3}, {%4,%5}, {%6}, {%0,%1,%2,%3};"
        : "+f"(d[0]), "+f"(d[1]), "+f"(d[2]), "+f"(d[3])
        : "r"(a0), "r"(a1), "r"(b0));
}
__device__ __forceinline__ uint32_t pack_bf16(float lo, float hi) {
    uint32_t r;
    asm("cvt.rn.bf16x2.f32 %0, %1, %2;" : "=r"(r) : "f"(hi), "f"(lo));
    return r;
}
__device__ __forceinline__ float ex2(float x) {
    float y;
    asm("ex2.approx.ftz.f32 %0, %1;" : "=f"(y) : "f"(x));
    return y;
}
__device__ __forceinline__ float rcp_approx(float x) {
    float y;
    asm("rcp.approx.ftz.f32 %0, %1;" : "=f"(y) : "f"(x));
    return y;
}
__device__ __forceinline__ uint32_t enc(float x) { return max(~__float_as_uint(x), 1u); }
__device__ __forceinline__ float dec(uint32_t u) { return __uint_as_float(~u); }
__device__ __forceinline__ void st_zero_v4(uint4* p) {
    asm volatile("st.relaxed.gpu.global.v4.u32 [%0], {0, 0, 0, 0};" ::"l"(p) : "memory");
}
__device__ __forceinline__ void st_pred_v4(uint4* p, uint32_t a, uint32_t b, uint32_t c, uint32_t d, bool pred) {
    asm volatile("{\n.reg .pred p;\nsetp.ne.u32 p, %5, 0;\n@p st.relaxed.gpu.global.v4.u32 [%0], {%1,%2,%3,%4};\n}\n"
                 ::"l"(p), "r"(a), "r"(b), "r"(c), "r"(d), "r"((uint32_t)pred) : "memory");
}
__device__ __forceinline__ void ld_pred_v4(uint4& v, const uint4* p, bool pred) {
    asm volatile("{\n.reg .pred p;\nsetp.ne.u32 p, %5, 0;\n@p ld.relaxed.gpu.global.v4.u32 {%0,%1,%2,%3}, [%4];\n}\n"
                 : "+r"(v.x), "+r"(v.y), "+r"(v.z), "+r"(v.w) : "l"(p), "r"((uint32_t)pred) : "memory");
}
__device__ __forceinline__ void st_pred_u16(void* p, uint16_t v, bool pred) {
    asm volatile("{\n.reg .pred p;\nsetp.ne.u32 p, %2, 0;\n@p st.global.u16 [%0], %1;\n}\n"
                 ::"l"(p), "h"(v), "r"((uint32_t)pred) : "memory");
}
__device__ __forceinline__ void st_pred_zero_v2(void* p, bool pred) {
    asm volatile("{\n.reg .pred p;\nsetp.ne.u32 p, %1, 0;\n@p st.relaxed.gpu.global.v2.u32 [%0], {0, 0};\n}\n"
                 ::"l"(p), "r"((uint32_t)pred) : "memory");
}
__device__ __forceinline__ uint32_t atom_inc(unsigned int* p) {
    uint32_t v;
    asm volatile("{\n.reg .u32 t;\nmov.u32 t, %laneid;\nadd.u32 t, t, 1;\n"
                 "atom.relaxed.gpu.global.add.u32 %0, [%1], t;\n}\n" : "=r"(v) : "l"(p) : "memory");
    return v;
}
__device__ __forceinline__ uint32_t min4(const uint4& v) { return min(min(v.x, v.y), min(v.z, v.w)); }
__device__ __forceinline__ float warp_max_f32(float x) {
    int k = __float_as_int(x);
    k ^= (k >> 31) & 0x7fffffff;
    k = __reduce_max_sync(0xffffffffu, k);
    k ^= (k >> 31) & 0x7fffffff;
    return __int_as_float(k);
}
__device__ __forceinline__ uint16_t bf16_bits(float x) { return __bfloat16_as_ushort(__float2bfloat16(x)); }

__global__ void __launch_bounds__(NTHREADS, 1)
paged_decode_kernel(const __grid_constant__ CUtensorMap tmK, const __grid_constant__ CUtensorMap tmV,
                    const __nv_bfloat16* __restrict__ q, const int* __restrict__ bt,
                    const int* __restrict__ ctx, __nv_bfloat16* __restrict__ out, int nb, int nsplit) {
    extern __shared__ uint8_t smem_raw[];
    const uint32_t sbase = (smem_u32(smem_raw) + 1023u) & ~1023u;
    const uint32_t sbt_base = sbase + NST * 2 * TILE;
    const uint32_t bar_base = sbt_base + SBT_MAX * 4;
    auto fullK = [&](int s) { return bar_base + 8u * s; };
    auto fullV = [&](int s) { return bar_base + 8u * (NST + s); };
    auto emptyK = [&](int s) { return bar_base + 8u * (2 * NST + s); };
    auto emptyV = [&](int s) { return bar_base + 8u * (3 * NST + s); };
    const uint32_t btbar = bar_base + 8u * (4 * NST);
    const uint32_t rdybar = bar_base + 8u * (4 * NST + 1);
    auto slot = [&](int s) { return bar_base + 8u * (4 * NST + 2) + 4u * s; };
    const uint32_t sstat = bar_base + 8u * (4 * NST + 2) + 4u * NST;

    const int warp = threadIdx.x >> 5;
    const int lane = threadIdx.x & 31;
    const int group = blockIdx.x % NGROUP;
    const int split = blockIdx.x / NGROUP;

    if (threadIdx.x == 0) {
        asm volatile("prefetch.tensormap [%0];" ::"l"(&tmK) : "memory");
        asm volatile("prefetch.tensormap [%0];" ::"l"(&tmV) : "memory");
    }
    int e0 = 0, ctx_raw;
    {
        const int idx0 = (split + (int)threadIdx.x * nsplit) / UPP;
        const uint32_t pr = (threadIdx.x < NST && idx0 < nb) ? 1u : 0u;
        asm volatile("{\n.reg .pred p;\nsetp.ne.u32 p, %2, 0;\n@p ld.global.nc.u32 %0, [%1];\n}\n"
                     : "+r"(e0) : "l"(bt + (pr ? idx0 : 0)), "r"(pr));
        asm volatile("ld.global.nc.u32 %0, [%1];" : "=r"(ctx_raw) : "l"(ctx));
    }
    if (threadIdx.x == 0) {
#pragma unroll
        for (int s = 0; s < NST; s++) {
            mbar_init(fullK(s), 1);
            mbar_init(fullV(s), 1);
            mbar_init(emptyK(s), NCW);
            mbar_init(emptyV(s), NCW);
        }
        mbar_init(btbar, 1);
        mbar_init(rdybar, 2);
        asm volatile("fence.mbarrier_init.release.cluster;" ::: "memory");
        asm volatile("fence.proxy.async.shared::cta;" ::: "memory");
    }
    if (warp == 0) {
        __syncwarp();
        asm volatile("bar.arrive 1, %0;" ::"n"(NTHREADS) : "memory");
    }

    if (warp == NCW + 1) {
        asm volatile("bar.sync 1, %0;" ::"n"(NTHREADS) : "memory");
        uint4* po = &g_scr_o[((group * NREADER + (lane >> 1)) * PMAX + split) * 2 + (lane & 1)];
#pragma unroll
        for (int k = 0; k < NREADER / 16; k++) st_zero_v4(po + k * 16 * PMAX * 2);
        if (lane < 2 * G) st_zero_v4(&g_scr_ml[((group * G + (lane >> 1)) * PMAX + split) * 2 + (lane & 1)]);
        __threadfence();
        __syncwarp();
        if (lane == 0) {
            unsigned int* ready = &g_ticket[group * 32 + 1];
            asm volatile("red.relaxed.gpu.global.add.u32 [%0], 1;" ::"l"(ready) : "memory");
            uint32_t spins = 0;
            while (true) {
                unsigned int v;
                asm volatile("ld.acquire.gpu.global.u32 %0, [%1];" : "=r"(v) : "l"(ready) : "memory");
                if (v >= (unsigned int)nsplit) break;
                if (++spins > (1u << 21)) __trap();
                __nanosleep(500);
            }
            mbar_arrive(rdybar);
            DBG(7);
        }
        return;
    }

    if (warp != 0) {
        const int cw = warp - 1;
        const int g = lane >> 2;
        const int t = lane & 3;
        const int kvh = group * G + cw;

        uint32_t qa[8][2];
        {
            const uint32_t* qp = reinterpret_cast<const uint32_t*>(q + (size_t)(kvh * 2 + (g & 1)) * DH);
#pragma unroll
            for (int ks = 0; ks < 8; ks++) {
                uint32_t v0 = __ldg(qp + ks * 8 + t);
                uint32_t v1 = __ldg(qp + ks * 8 + 4 + t);
                qa[ks][0] = (g < 2) ? v0 : 0u;
                qa[ks][1] = (g < 2) ? v1 : 0u;
            }
        }
        asm volatile("bar.sync 1, %0;" ::"n"(NTHREADS) : "memory");

        const int lk = nb * BS;
        const bool uniform = (ctx_raw <= 0);
        const int len = uniform ? lk : min(ctx_raw, lk);
        const float cscale = 0.08838834764831845f * 1.4426950408889634f;

        float o[8][4];
#pragma unroll
        for (int i = 0; i < 8; i++) { o[i][0] = o[i][1] = o[i][2] = o[i][3] = 0.f; }
        float m_run = -INFINITY;
        float l_run = 0.f;

        const int r8 = lane & 7;
        const int mi = lane >> 3;
        const uint32_t lane_off = (uint32_t)(cw * 2 * CHUNK + r8 * 128);

        int st = 0;
        uint32_t ph = 0;
#pragma unroll 1
        for (int it = 0;; it++) {
            const uint32_t kb = sbase + st * 2 * TILE + lane_off;
            const uint32_t vb = kb + TILE;
            mbar_wait(fullK(st), ph);
            const uint32_t info = lds_u32(slot(st));
            const bool last = (info & INFO_LAST) != 0;
            const bool empty = (info & INFO_EMPTY) != 0;
            const bool epi = last || it == WARM_IT;
            uint32_t pb = 0;
            if (!empty) {
                float s0[4] = {0.f, 0.f, 0.f, 0.f}, s1[4] = {0.f, 0.f, 0.f, 0.f};
#pragma unroll
                for (int c = 0; c < 2; c++) {
#pragma unroll
                    for (int hf = 0; hf < 2; hf++) {
                        uint32_t b0, b1, b2, b3;
                        ldsm_x4(b0, b1, b2, b3, kb + c * CHUNK + (uint32_t)(((hf * 4 + mi) ^ r8) << 4));
                        const int ks = c * 4 + hf * 2;
                        if (c == 0) {
                            mma_k16(s0, qa[ks][0], 0u, qa[ks][1], 0u, b0, b1);
                            mma_k16(s0, qa[ks + 1][0], 0u, qa[ks + 1][1], 0u, b2, b3);
                        } else {
                            mma_k16(s1, qa[ks][0], 0u, qa[ks][1], 0u, b0, b1);
                            mma_k16(s1, qa[ks + 1][0], 0u, qa[ks + 1][1], 0u, b2, b3);
                        }
                    }
                }
                __syncwarp();
                if (lane == 0) mbar_arrive(emptyK(st));

                float sv0 = s0[0] + s1[0];
                float sv1 = s0[1] + s1[1];
                const int tok0 = (int)(info & INFO_MASK) * TOK;
                if (uniform) { sv0 = 0.f; sv1 = 0.f; }
                if (tok0 + TOK > len) {
                    const int tb = tok0 + 2 * t;
                    if (tb >= len) sv0 = -INFINITY;
                    if (tb + 1 >= len) sv1 = -INFINITY;
                }
                float mx = fmaxf(sv0, sv1);
                mx = fmaxf(mx, __shfl_xor_sync(0xffffffffu, mx, 1));
                mx = fmaxf(mx, __shfl_xor_sync(0xffffffffu, mx, 2));
                const float m_new = fmaxf(m_run, mx);
                const float m_use = (m_new == -INFINITY) ? 0.f : m_new;
                const float alpha = ex2((m_run - m_use) * cscale);
                const float mc = m_use * cscale;
                const float p0 = ex2(fmaf(sv0, cscale, -mc));
                const float p1 = ex2(fmaf(sv1, cscale, -mc));
                m_run = m_new;
                l_run = fmaf(l_run, alpha, p0 + p1);
                pb = pack_bf16(p0, p1);
                const float a0 = __shfl_sync(0xffffffffu, alpha, 0);
                const float a1 = __shfl_sync(0xffffffffu, alpha, 4);
                if (a0 != 1.f || a1 != 1.f) {
#pragma unroll
                    for (int i = 0; i < 8; i++) {
                        o[i][0] *= a0; o[i][1] *= a1; o[i][2] *= a0; o[i][3] *= a1;
                    }
                }
            }
            if (epi) {
                if (last) mbar_wait(rdybar, 0);
                float l = l_run;
                l += __shfl_xor_sync(0xffffffffu, l, 1);
                l += __shfl_xor_sync(0xffffffffu, l, 2);
                const float mc = m_run * cscale;
                const float m0 = __shfl_sync(0xffffffffu, mc, 0);
                const float m1 = __shfl_sync(0xffffffffu, mc, 4);
                const float l0 = __shfl_sync(0xffffffffu, l, 0);
                const float l1 = __shfl_sync(0xffffffffu, l, 4);
                st_pred_v4(&g_scr_ml[(kvh * PMAX + split) * 2 + (lane & 1)], enc(m0), enc(m1), enc(l0), enc(l1),
                           last && lane < 2);
            }
            if (!empty) {
                mbar_wait(fullV(st), ph);
#pragma unroll
                for (int mp = 0; mp < 4; mp++) {
                    uint32_t a0r, a1r, a2r, a3r;
                    ldsm_x4_t(a0r, a1r, a2r, a3r, vb + (mp >> 1) * CHUNK + (uint32_t)((((mp & 1) * 4 + mi) ^ r8) << 4));
                    mma_k8(o[2 * mp], a0r, a1r, pb);
                    mma_k8(o[2 * mp + 1], a2r, a3r, pb);
                }
                __syncwarp();
                if (lane == 0) mbar_arrive(emptyV(st));
            }
            if (epi) {
                {
                    uint4* po = &g_scr_o[((kvh * 32 + (g >> 1)) * PMAX + split) * 2 + (g & 1)];
                    const bool pr = last && t == 0;
#pragma unroll
                    for (int mt = 0; mt < 8; mt++) {
                        st_pred_v4(po + mt * 4 * PMAX * 2, enc(o[mt][0]), enc(o[mt][1]), enc(o[mt][2]), enc(o[mt][3]), pr);
                    }
                }
#pragma unroll 1
                for (int ri = (cw < RW) ? split * RW + cw : NREADER; ri < NREADER; ri += nsplit * RW) {
                    const int ii = lane >> 1;
                    const int gg = lane & 1;
                    const int j = group * G + (ri >> 5);
                    const int mt = (ri >> 2) & 7;
                    const int gq = (ri & 3) * 2 + gg;
                    const uint4* po = &g_scr_o[((group * NREADER + ri) * PMAX + ii) * 2 + gg];
                    const uint4* pm = &g_scr_ml[(j * PMAX + ii) * 2];
                    uint4 ov[PROUNDS], mv[PROUNDS];
#pragma unroll
                    for (int r = 0; r < PROUNDS; r++) {
                        const bool present = last && (r * PPR + ii < nsplit);
                        ov[r].x = ov[r].y = ov[r].z = ov[r].w = present ? 0u : 0xffffffffu;
                        mv[r].x = mv[r].y = present ? 0u : 0x007fffffu;
                        mv[r].z = mv[r].w = present ? 0u : 0xffffffffu;
                    }
                    uint32_t spins = 0;
                    while (true) {
                        bool anyneed = false;
#pragma unroll
                        for (int r = 0; r < PROUNDS; r++) {
                            const bool need = min(min4(ov[r]), min4(mv[r])) == 0u;
                            anyneed |= need;
                            ld_pred_v4(ov[r], po + r * PPR * 2, need);
                            ld_pred_v4(mv[r], pm + r * PPR * 2, need);
                        }
                        if (!__any_sync(0xffffffffu, anyneed)) break;
                        if (++spins > (1u << 22)) __trap();
                    }
                    float M0 = -INFINITY, M1 = -INFINITY;
#pragma unroll
                    for (int r = 0; r < PROUNDS; r++) {
                        M0 = fmaxf(M0, dec(mv[r].x));
                        M1 = fmaxf(M1, dec(mv[r].y));
                    }
                    M0 = warp_max_f32(M0);
                    M1 = warp_max_f32(M1);
                    if (M0 == -INFINITY) M0 = 0.f;
                    if (M1 == -INFINITY) M1 = 0.f;
                    float L0 = 0.f, L1 = 0.f, acc0 = 0.f, acc1 = 0.f, acc2 = 0.f, acc3 = 0.f;
#pragma unroll
                    for (int r = 0; r < PROUNDS; r++) {
                        const float w0 = ex2(dec(mv[r].x) - M0);
                        const float w1 = ex2(dec(mv[r].y) - M1);
                        L0 = fmaf(w0, dec(mv[r].z), L0);
                        L1 = fmaf(w1, dec(mv[r].w), L1);
                        acc0 = fmaf(w0, dec(ov[r].x), acc0);
                        acc1 = fmaf(w1, dec(ov[r].y), acc1);
                        acc2 = fmaf(w0, dec(ov[r].z), acc2);
                        acc3 = fmaf(w1, dec(ov[r].w), acc3);
                    }
#pragma unroll
                    for (int d = 2; d <= 16; d <<= 1) {
                        L0 += __shfl_xor_sync(0xffffffffu, L0, d);
                        L1 += __shfl_xor_sync(0xffffffffu, L1, d);
                        acc0 += __shfl_xor_sync(0xffffffffu, acc0, d);
                        acc1 += __shfl_xor_sync(0xffffffffu, acc1, d);
                        acc2 += __shfl_xor_sync(0xffffffffu, acc2, d);
                        acc3 += __shfl_xor_sync(0xffffffffu, acc3, d);
                    }
                    const float i0 = rcp_approx(L0), i1 = rcp_approx(L1);
                    __nv_bfloat16* o0 = out + (size_t)(2 * j) * DH + mt * 16 + gq;
                    const bool pr = last && ii == 0;
                    st_pred_u16(o0, bf16_bits(acc0 * i0), pr);
                    st_pred_u16(o0 + DH, bf16_bits(acc1 * i1), pr);
                    st_pred_u16(o0 + 8, bf16_bits(acc2 * i0), pr);
                    st_pred_u16(o0 + DH + 8, bf16_bits(acc3 * i1), pr);
                    st_pred_zero_v2(&g_ticket[group * 32], last && ri == 0 && lane == 0);
                }
                if (last) break;
            }
            if (++st == NST) { st = 0; ph ^= 1; }
        }
        if (threadIdx.x == 32) DBG(5);
        return;
    }

    {
        if (lane < NST) sts_u32(sstat + 4u * lane, (uint32_t)e0);
        __syncwarp();
        if (lane != 0) return;

        uint64_t pol;
        asm volatile("createpolicy.fractional.L2::evict_first.b64 %0, 1.0;" : "=l"(pol));
        unsigned int* ticket = &g_ticket[group * 32];
        const int dyn_base = NST * nsplit;
        const int nstage_bt = min(nb, SBT_MAX) & ~3;
        const int lk = nb * BS;
        const int len = (ctx_raw <= 0) ? lk : min(ctx_raw, lk);
        const int nunits = (len + TOK - 1) / TOK;
        int q0 = split;
        if (q0 >= nunits) {
            sts_u32(slot(0), INFO_LAST | INFO_EMPTY);
            mbar_arrive(fullK(0));
        } else {
            int q1 = q0 + nsplit;
            int st = 0;
            uint32_t ph = 1;
            int u = 0;
#pragma unroll 1
            for (;; u++) {
                const int uidx = q0;
                q0 = q1 + (u + 1 < NST ? 0 : dyn_base);
                const bool last = q0 >= nunits;
                if (!last) {
                    if (u + 2 < NST) q1 += nsplit;
                    else q1 = (int)atom_inc(ticket);
                }
                const int pidx = uidx / UPP;
                int page;
                if (u < NST) {
                    page = (int)lds_u32(sstat + 4u * u);
                } else {
                    if (u == NST && nstage_bt > 0) mbar_wait(btbar, 0);
                    page = (pidx < nstage_bt) ? (int)lds_u32(sbt_base + pidx * 4) : __ldg(bt + pidx);
                }
                const int row = page * BS + (uidx % UPP) * TOK;
                const uint32_t kdst = sbase + st * 2 * TILE;
                mbar_wait(emptyK(st), ph);
                sts_u32(slot(st), (uint32_t)uidx | (last ? INFO_LAST : 0u));
                mbar_expect_tx(fullK(st), TILE);
                tma_load_3d(kdst, &tmK, row, group * 2 * G, fullK(st), pol);
                mbar_wait(emptyV(st), ph);
                mbar_expect_tx(fullV(st), TILE);
                tma_load_3d(kdst + TILE, &tmV, row, group * 2 * G, fullV(st), pol);
                if (u == 0) {
                    DBG(1);
                    if (nstage_bt > 0) {
                        mbar_expect_tx(btbar, nstage_bt * 4);
                        bulk_g2s(sbt_base, bt, nstage_bt * 4, btbar);
                    }
                }
                if (last) break;
                if (++st == NST) { st = 0; ph ^= 1; }
            }
            if (u < NST && nstage_bt > 0) mbar_wait(btbar, 0);
        }
        mbar_arrive(rdybar);
        DBG(2);
    }
}

typedef CUresult (*EncodeTiledFn)(CUtensorMap*, CUtensorMapDataType, cuuint32_t, void*, const cuuint64_t*,
                                  const cuuint64_t*, const cuuint32_t*, const cuuint32_t*, CUtensorMapInterleave,
                                  CUtensorMapSwizzle, CUtensorMapL2promotion, CUtensorMapFloatOOBfill);

bool make_map(EncodeTiledFn enc_fn, CUtensorMap* tm, const void* base, uint64_t rows) {
    cuuint64_t gd[3] = {64, rows, 32};
    cuuint64_t gs[2] = {4096, 128};
    cuuint32_t bd[3] = {64, (cuuint32_t)TOK, (cuuint32_t)(2 * G)};
    cuuint32_t es[3] = {1, 1, 1};
    return enc_fn(tm, CU_TENSOR_MAP_DATA_TYPE_BFLOAT16, 3, const_cast<void*>(base), gd, gs, bd, es,
                  CU_TENSOR_MAP_INTERLEAVE_NONE, CU_TENSOR_MAP_SWIZZLE_128B, CU_TENSOR_MAP_L2_PROMOTION_L2_256B,
                  CU_TENSOR_MAP_FLOAT_OOB_FILL_NONE) == CUDA_SUCCESS;
}

}

extern "C" void kernel_launch(void* const* d_in, const int* in_sizes, int n_in, void* d_out, int out_size) {
    (void)n_in; (void)out_size;
    const __nv_bfloat16* q = (const __nv_bfloat16*)d_in[0];
    const void* kc = d_in[1];
    const void* vc = d_in[2];
    const int* bt = (const int*)d_in[3];
    const int* ctx = (const int*)d_in[4];
    __nv_bfloat16* out = (__nv_bfloat16*)d_out;

    static EncodeTiledFn enc_fn = nullptr;
    static int num_sms = 0;
    if (!enc_fn) {
        void* fn = nullptr;
        cudaDriverEntryPointQueryResult qr;
        cudaGetDriverEntryPoint("cuTensorMapEncodeTiled", &fn, cudaEnableDefault, &qr);
        enc_fn = (EncodeTiledFn)fn;
        int dev = 0;
        cudaGetDevice(&dev);
        cudaDeviceGetAttribute(&num_sms, cudaDevAttrMultiProcessorCount, dev);
        cudaFuncSetAttribute(paged_decode_kernel, cudaFuncAttributeMaxDynamicSharedMemorySize, SMEM_BYTES);
    }
    const uint64_t rows = (uint64_t)in_sizes[1] / (HKV * DH);
    const int nb = in_sizes[3];
    CUtensorMap tmK, tmV;
    make_map(enc_fn, &tmK, kc, rows);
    make_map(enc_fn, &tmV, vc, rows);
    int nsplit = num_sms / NGROUP;
    if (nsplit > MAX_SPLIT) nsplit = MAX_SPLIT;
    if (nsplit < 1) nsplit = 1;
    paged_decode_kernel<<<nsplit * NGROUP, NTHREADS, SMEM_BYTES, cudaStreamPerThread>>>(tmK, tmV, q, bt, ctx, out, nb, nsplit);
}
```

```cpp
#include <cuda_runtime.h>
#include <cuda_bf16.h>
#include <cuda.h>
#include <stdint.h>

namespace {

constexpr int HKV = 16;
constexpr int DH = 128;
constexpr int BS = 16;
constexpr int G = 8;
constexpr int TOK = 8;
constexpr int UPP = BS / TOK;
constexpr int NGROUP = HKV / G;
constexpr int NST = 3;
constexpr int CHUNK = TOK * 128;
constexpr int TILE = G * 2 * CHUNK;
constexpr int NCW = G;
constexpr int NTHREADS = (NCW + 2) * 32;
constexpr int MAX_SMS = 132;
constexpr int MAX_SPLIT = MAX_SMS / NGROUP;
constexpr int PPR = 16;
constexpr int PROUNDS = (MAX_SPLIT + PPR - 1) / PPR;
constexpr int PMAX = PROUNDS * PPR;
constexpr int NITEM = HKV * 8 * 4;
constexpr int NREADER = G * 8 * 4;
constexpr int RW = 4;
constexpr uint32_t INFO_EMPTY = 0x80000000u;
constexpr int SBT_MAX = 4096;
constexpr int SMEM_BYTES = NST * 2 * TILE + SBT_MAX * 4 + 1024 + 512;
constexpr int WARM_IT = 2;

__device__ uint4 g_scr_o[NITEM * PMAX * 2];
__device__ uint4 g_scr_ml[HKV * PMAX * 2];
__device__ unsigned int g_ticket[NGROUP * 32];

#define DBG(slot) do {} while (0)

__device__ __forceinline__ uint32_t smem_u32(const void* p) { return (uint32_t)__cvta_generic_to_shared(p); }

__device__ __forceinline__ void mbar_init(uint32_t bar, uint32_t cnt) {
    asm volatile("mbarrier.init.shared::cta.b64 [%0], %1;" ::"r"(bar), "r"(cnt) : "memory");
}
__device__ __forceinline__ void mbar_expect_tx(uint32_t bar, uint32_t bytes) {
    asm volatile("mbarrier.arrive.expect_tx.shared::cta.b64 _, [%0], %1;" ::"r"(bar), "r"(bytes) : "memory");
}
__device__ __forceinline__ void mbar_arrive(uint32_t bar) {
    asm volatile("mbarrier.arrive.shared::cta.b64 _, [%0];" ::"r"(bar) : "memory");
}
__device__ __forceinline__ bool mbar_try_wait(uint32_t bar, uint32_t parity) {
    uint32_t ok;
    asm volatile(
        "{\n.reg .pred p;\n"
        "mbarrier.try_wait.parity.shared::cta.b64 p, [%1], %2;\n"
        "selp.u32 %0, 1, 0, p;\n}\n"
        : "=r"(ok)
        : "r"(bar), "r"(parity)
        : "memory");
    return ok != 0;
}
__device__ __forceinline__ void mbar_wait(uint32_t bar, uint32_t parity) {
    uint32_t spins = 0;
    while (!mbar_try_wait(bar, parity)) {
        if (++spins > (1u << 22)) __trap();
    }
}
__device__ __forceinline__ void tma_load_3d(uint32_t dst, const CUtensorMap* tm, int row, int chunk, uint32_t bar, uint64_t pol) {
    asm volatile(
        "cp.async.bulk.tensor.3d.shared::cluster.global.mbarrier::complete_tx::bytes.L2::cache_hint "
        "[%0], [%1, {%3, %4, %5}], [%2], %6;"
        ::"r"(dst), "l"(tm), "r"(bar), "r"(0), "r"(row), "r"(chunk), "l"(pol)
        : "memory");
}
__device__ __forceinline__ void bulk_g2s(uint32_t dst, const void* src, uint32_t bytes, uint32_t bar) {
    asm volatile("cp.async.bulk.shared::cluster.global.mbarrier::complete_tx::bytes [%0], [%1], %2, [%3];"
                 ::"r"(dst), "l"(src), "r"(bytes), "r"(bar) : "memory");
}
__device__ __forceinline__ void sts_u32(uint32_t addr, uint32_t v) {
    asm volatile("st.shared.u32 [%0], %1;" ::"r"(addr), "r"(v) : "memory");
}
__device__ __forceinline__ uint32_t lds_u32(uint32_t addr) {
    uint32_t v;
    asm volatile("ld.shared.u32 %0, [%1];" : "=r"(v) : "r"(addr) : "memory");
    return v;
}
__device__ __forceinline__ void ldsm_x4(uint32_t& r0, uint32_t& r1, uint32_t& r2, uint32_t& r3, uint32_t addr) {
    asm volatile("ldmatrix.sync.aligned.m8n8.x4.shared.b16 {%0,%1,%2,%3}, [%4];"
                 : "=r"(r0), "=r"(r1), "=r"(r2), "=r"(r3) : "r"(addr) : "memory");
}
__device__ __forceinline__ void ldsm_x4_t(uint32_t& r0, uint32_t& r1, uint32_t& r2, uint32_t& r3, uint32_t addr) {
    asm volatile("ldmatrix.sync.aligned.m8n8.x4.trans.shared.b16 {%0,%1,%2,%3}, [%4];"
                 : "=r"(r0), "=r"(r1), "=r"(r2), "=r"(r3) : "r"(addr) : "memory");
}
__device__ __forceinline__ void mma_k16(float (&d)[4], uint32_t a0, uint32_t a1, uint32_t a2, uint32_t a3,
                                        uint32_t b0, uint32_t b1) {
    asm volatile(
        "mma.sync.aligned.m16n8k16.row.col.f32.bf16.bf16.f32 {%0,%1,%2,%3}, {%4,%5,%6,%7}, {%8,%9}, {%0,%1,%2,%3};"
        : "+f"(d[0]), "+f"(d[1]), "+f"(d[2]), "+f"(d[3])
        : "r"(a0), "r"(a1), "r"(a2), "r"(a3), "r"(b0), "r"(b1));
}
__device__ __forceinline__ void mma_k8(float (&d)[4], uint32_t a0, uint32_t a1, uint32_t b0) {
    asm volatile(
        "mma.sync.aligned.m16n8k8.row.col.f32.bf16.bf16.f32 {%0,%1,%2,%3}, {%4,%5}, {%6}, {%0,%1,%2,%3};"
        : "+f"(d[0]), "+f"(d[1]), "+f"(d[2]), "+f"(d[3])
        : "r"(a0), "r"(a1), "r"(b0));
}
__device__ __forceinline__ uint32_t pack_bf16(float lo, float hi) {
    uint32_t r;
    asm("cvt.rn.bf16x2.f32 %0, %1, %2;" : "=r"(r) : "f"(hi), "f"(lo));
    return r;
}
__device__ __forceinline__ float ex2(float x) {
    float y;
    asm("ex2.approx.ftz.f32 %0, %1;" : "=f"(y) : "f"(x));
    return y;
}
__device__ __forceinline__ float rcp_approx(float x) {
    float y;
    asm("rcp.approx.ftz.f32 %0, %1;" : "=f"(y) : "f"(x));
    return y;
}
__device__ __forceinline__ uint32_t enc(float x) { return max(~__float_as_uint(x), 1u); }
__device__ __forceinline__ float dec(uint32_t u) { return __uint_as_float(~u); }
__device__ __forceinline__ void st_zero_v4(uint4* p) {
    asm volatile("st.relaxed.gpu.global.v4.u32 [%0], {0, 0, 0, 0};" ::"l"(p) : "memory");
}
__device__ __forceinline__ void st_pred_v4(uint4* p, uint32_t a, uint32_t b, uint32_t c, uint32_t d, bool pred) {
    asm volatile("{\n.reg .pred p;\nsetp.ne.u32 p, %5, 0;\n@p st.relaxed.gpu.global.v4.u32 [%0], {%1,%2,%3,%4};\n}\n"
                 ::"l"(p), "r"(a), "r"(b), "r"(c), "r"(d), "r"((uint32_t)pred) : "memory");
}
__device__ __forceinline__ void ld_pred_v4(uint4& v, const uint4* p, bool pred) {
    asm volatile("{\n.reg .pred p;\nsetp.ne.u32 p, %5, 0;\n@p ld.relaxed.gpu.global.v4.u32 {%0,%1,%2,%3}, [%4];\n}\n"
                 : "+r"(v.x), "+r"(v.y), "+r"(v.z), "+r"(v.w) : "l"(p), "r"((uint32_t)pred) : "memory");
}
__device__ __forceinline__ void st_pred_u16(void* p, uint16_t v, bool pred) {
    asm volatile("{\n.reg .pred p;\nsetp.ne.u32 p, %2, 0;\n@p st.global.u16 [%0], %1;\n}\n"
                 ::"l"(p), "h"(v), "r"((uint32_t)pred) : "memory");
}
__device__ __forceinline__ void st_pred_zero_v2(void* p, bool pred) {
    asm volatile("{\n.reg .pred p;\nsetp.ne.u32 p, %1, 0;\n@p st.relaxed.gpu.global.v2.u32 [%0], {0, 0};\n}\n"
                 ::"l"(p), "r"((uint32_t)pred) : "memory");
}
__device__ __forceinline__ uint32_t atom_inc(unsigned int* p) {
    uint32_t v;
    asm volatile("{\n.reg .u32 t;\nmov.u32 t, %laneid;\nadd.u32 t, t, 1;\n"
                 "atom.relaxed.gpu.global.add.u32 %0, [%1], t;\n}\n" : "=r"(v) : "l"(p) : "memory");
    return v;
}
__device__ __forceinline__ uint32_t min4(const uint4& v) { return min(min(v.x, v.y), min(v.z, v.w)); }
__device__ __forceinline__ float warp_max_f32(float x) {
    int k = __float_as_int(x);
    k ^= (k >> 31) & 0x7fffffff;
    k = __reduce_max_sync(0xffffffffu, k);
    k ^= (k >> 31) & 0x7fffffff;
    return __int_as_float(k);
}
__device__ __forceinline__ uint16_t bf16_bits(float x) { return __bfloat16_as_ushort(__float2bfloat16(x)); }

__global__ void __launch_bounds__(NTHREADS, 1)
paged_decode_kernel(const __grid_constant__ CUtensorMap tmK, const __grid_constant__ CUtensorMap tmV,
                    const __nv_bfloat16* __restrict__ q, const int* __restrict__ bt,
                    const int* __restrict__ ctx, __nv_bfloat16* __restrict__ out, int nb, int nsplit) {
    extern __shared__ uint8_t smem_raw[];
    const uint32_t sbase = (smem_u32(smem_raw) + 1023u) & ~1023u;
    const uint32_t sbt_base = sbase + NST * 2 * TILE;
    const uint32_t bar_base = sbt_base + SBT_MAX * 4;
    auto fullK = [&](int s) { return bar_base + 8u * s; };
    auto fullV = [&](int s) { return bar_base + 8u * (NST + s); };
    auto emptyK = [&](int s) { return bar_base + 8u * (2 * NST + s); };
    auto emptyV = [&](int s) { return bar_base + 8u * (3 * NST + s); };
    const uint32_t btbar = bar_base + 8u * (4 * NST);
    const uint32_t rdybar = bar_base + 8u * (4 * NST + 1);
    auto slot = [&](int s) { return bar_base + 8u * (4 * NST + 2) + 4u * s; };
    const uint32_t sstat = bar_base + 8u * (4 * NST + 2) + 4u * NST;
    const uint32_t lastseq = sstat + 4u * NST;

    const int warp = threadIdx.x >> 5;
    const int lane = threadIdx.x & 31;
    const int group = blockIdx.x % NGROUP;
    const int split = blockIdx.x / NGROUP;

    if (threadIdx.x == 0) {
        asm volatile("prefetch.tensormap [%0];" ::"l"(&tmK) : "memory");
        asm volatile("prefetch.tensormap [%0];" ::"l"(&tmV) : "memory");
    }
    int e0 = 0, ctx_raw;
    {
        const int idx0 = (split + (int)threadIdx.x * nsplit) / UPP;
        const uint32_t pr = (threadIdx.x < NST && idx0 < nb) ? 1u : 0u;
        asm volatile("{\n.reg .pred p;\nsetp.ne.u32 p, %2, 0;\n@p ld.global.nc.u32 %0, [%1];\n}\n"
                     : "+r"(e0) : "l"(bt + (pr ? idx0 : 0)), "r"(pr));
        asm volatile("ld.global.nc.u32 %0, [%1];" : "=r"(ctx_raw) : "l"(ctx));
    }
    if (threadIdx.x == 0) {
#pragma unroll
        for (int s = 0; s < NST; s++) {
            mbar_init(fullK(s), 1);
            mbar_init(fullV(s), 1);
            mbar_init(emptyK(s), NCW);
            mbar_init(emptyV(s), NCW);
        }
        mbar_init(btbar, 1);
        mbar_init(rdybar, 2);
        sts_u32(lastseq, 0xffffffffu);
        asm volatile("fence.mbarrier_init.release.cluster;" ::: "memory");
        asm volatile("fence.proxy.async.shared::cta;" ::: "memory");
    }
    if (warp == 0) {
        __syncwarp();
        asm volatile("bar.arrive 1, %0;" ::"n"(NTHREADS) : "memory");
    }

    if (warp == NCW + 1) {
        asm volatile("bar.sync 1, %0;" ::"n"(NTHREADS) : "memory");
        uint4* po = &g_scr_o[((group * NREADER + (lane >> 1)) * PMAX + split) * 2 + (lane & 1)];
#pragma unroll
        for (int k = 0; k < NREADER / 16; k++) st_zero_v4(po + k * 16 * PMAX * 2);
        if (lane < 2 * G) st_zero_v4(&g_scr_ml[((group * G + (lane >> 1)) * PMAX + split) * 2 + (lane & 1)]);
        __threadfence();
        __syncwarp();
        if (lane == 0) {
            unsigned int* ready = &g_ticket[group * 32 + 1];
            asm volatile("red.relaxed.gpu.global.add.u32 [%0], 1;" ::"l"(ready) : "memory");
            uint32_t spins = 0;
            while (true) {
                unsigned int v;
                asm volatile("ld.acquire.gpu.global.u32 %0, [%1];" : "=r"(v) : "l"(ready) : "memory");
                if (v >= (unsigned int)nsplit) break;
                if (++spins > (1u << 21)) __trap();
                __nanosleep(500);
            }
            mbar_arrive(rdybar);
            DBG(7);
        }
        return;
    }

    if (warp != 0) {
        const int cw = warp - 1;
        const int g = lane >> 2;
        const int t = lane & 3;
        const int kvh = group * G + cw;

        uint32_t qa[8][2];
        {
            const uint32_t* qp = reinterpret_cast<const uint32_t*>(q + (size_t)(kvh * 2 + (g & 1)) * DH);
#pragma unroll
            for (int ks = 0; ks < 8; ks++) {
                uint32_t v0 = __ldg(qp + ks * 8 + t);
                uint32_t v1 = __ldg(qp + ks * 8 + 4 + t);
                qa[ks][0] = (g < 2) ? v0 : 0u;
                qa[ks][1] = (g < 2) ? v1 : 0u;
            }
        }
        asm volatile("bar.sync 1, %0;" ::"n"(NTHREADS) : "memory");

        const int lk = nb * BS;
        const bool uniform = (ctx_raw <= 0);
        const int len = uniform ? lk : min(ctx_raw, lk);
        const float cscale = 0.08838834764831845f * 1.4426950408889634f;

        float o[8][4];
#pragma unroll
        for (int i = 0; i < 8; i++) { o[i][0] = o[i][1] = o[i][2] = o[i][3] = 0.f; }
        float m_run = -INFINITY;
        float l_run = 0.f;

        const int r8 = lane & 7;
        const int mi = lane >> 3;
        const uint32_t lane_off = (uint32_t)(cw * 2 * CHUNK + r8 * 128);

        int st = 0;
        uint32_t ph = 0;
#pragma unroll 1
        for (int it = 0;; it++) {
            const uint32_t kb = sbase + st * 2 * TILE + lane_off;
            const uint32_t vb = kb + TILE;
            mbar_wait(fullK(st), ph);
            const uint32_t info = lds_u32(slot(st));
            const bool empty = (info & INFO_EMPTY) != 0;
            const bool last = empty || lds_u32(lastseq) == (uint32_t)it;
            const bool epi = last || it == WARM_IT;
            uint32_t pb = 0;
            if (!empty) {
                float s0[4] = {0.f, 0.f, 0.f, 0.f}, s1[4] = {0.f, 0.f, 0.f, 0.f};
#pragma unroll
                for (int c = 0; c < 2; c++) {
#pragma unroll
                    for (int hf = 0; hf < 2; hf++) {
                        uint32_t b0, b1, b2, b3;
                        ldsm_x4(b0, b1, b2, b3, kb + c * CHUNK + (uint32_t)(((hf * 4 + mi) ^ r8) << 4));
                        const int ks = c * 4 + hf * 2;
                        if (c == 0) {
                            mma_k16(s0, qa[ks][0], 0u, qa[ks][1], 0u, b0, b1);
                            mma_k16(s0, qa[ks + 1][0], 0u, qa[ks + 1][1], 0u, b2, b3);
                        } else {
                            mma_k16(s1, qa[ks][0], 0u, qa[ks][1], 0u, b0, b1);
                            mma_k16(s1, qa[ks + 1][0], 0u, qa[ks + 1][1], 0u, b2, b3);
                        }
                    }
                }
                __syncwarp();
                if (lane == 0) mbar_arrive(emptyK(st));

                float sv0 = s0[0] + s1[0];
                float sv1 = s0[1] + s1[1];
                const int tok0 = (int)info * TOK;
                if (uniform) { sv0 = 0.f; sv1 = 0.f; }
                if (tok0 + TOK > len) {
                    const int tb = tok0 + 2 * t;
                    if (tb >= len) sv0 = -INFINITY;
                    if (tb + 1 >= len) sv1 = -INFINITY;
                }
                float mx = fmaxf(sv0, sv1);
                mx = fmaxf(mx, __shfl_xor_sync(0xffffffffu, mx, 1));
                mx = fmaxf(mx, __shfl_xor_sync(0xffffffffu, mx, 2));
                const float m_new = fmaxf(m_run, mx);
                const float m_use = (m_new == -INFINITY) ? 0.f : m_new;
                const float alpha = ex2((m_run - m_use) * cscale);
                const float mc = m_use * cscale;
                const float p0 = ex2(fmaf(sv0, cscale, -mc));
                const float p1 = ex2(fmaf(sv1, cscale, -mc));
                m_run = m_new;
                l_run = fmaf(l_run, alpha, p0 + p1);
                pb = pack_bf16(p0, p1);
                const float a0 = __shfl_sync(0xffffffffu, alpha, 0);
                const float a1 = __shfl_sync(0xffffffffu, alpha, 4);
                if (a0 != 1.f || a1 != 1.f) {
#pragma unroll
                    for (int i = 0; i < 8; i++) {
                        o[i][0] *= a0; o[i][1] *= a1; o[i][2] *= a0; o[i][3] *= a1;
                    }
                }
            }
            if (epi) {
                if (last) mbar_wait(rdybar, 0);
                float l = l_run;
                l += __shfl_xor_sync(0xffffffffu, l, 1);
                l += __shfl_xor_sync(0xffffffffu, l, 2);
                const float mc = m_run * cscale;
                const float m0 = __shfl_sync(0xffffffffu, mc, 0);
                const float m1 = __shfl_sync(0xffffffffu, mc, 4);
                const float l0 = __shfl_sync(0xffffffffu, l, 0);
                const float l1 = __shfl_sync(0xffffffffu, l, 4);
                st_pred_v4(&g_scr_ml[(kvh * PMAX + split) * 2 + (lane & 1)], enc(m0), enc(m1), enc(l0), enc(l1),
                           last && lane < 2);
            }
            if (!empty) {
                mbar_wait(fullV(st), ph);
#pragma unroll
                for (int mp = 0; mp < 4; mp++) {
                    uint32_t a0r, a1r, a2r, a3r;
                    ldsm_x4_t(a0r, a1r, a2r, a3r, vb + (mp >> 1) * CHUNK + (uint32_t)((((mp & 1) * 4 + mi) ^ r8) << 4));
                    mma_k8(o[2 * mp], a0r, a1r, pb);
                    mma_k8(o[2 * mp + 1], a2r, a3r, pb);
                }
                __syncwarp();
                if (lane == 0) mbar_arrive(emptyV(st));
            }
            if (epi) {
                {
                    uint4* po = &g_scr_o[((kvh * 32 + (g >> 1)) * PMAX + split) * 2 + (g & 1)];
                    const bool pr = last && t == 0;
#pragma unroll
                    for (int mt = 0; mt < 8; mt++) {
                        st_pred_v4(po + mt * 4 * PMAX * 2, enc(o[mt][0]), enc(o[mt][1]), enc(o[mt][2]), enc(o[mt][3]), pr);
                    }
                }
#pragma unroll 1
                for (int ri = (cw < RW) ? split * RW + cw : NREADER; ri < NREADER; ri += nsplit * RW) {
                    const int ii = lane >> 1;
                    const int gg = lane & 1;
                    const int j = group * G + (ri >> 5);
                    const int mt = (ri >> 2) & 7;
                    const int gq = (ri & 3) * 2 + gg;
                    const uint4* po = &g_scr_o[((group * NREADER + ri) * PMAX + ii) * 2 + gg];
                    const uint4* pm = &g_scr_ml[(j * PMAX + ii) * 2];
                    uint4 ov[PROUNDS], mv[PROUNDS];
#pragma unroll
                    for (int r = 0; r < PROUNDS; r++) {
                        const bool present = last && (r * PPR + ii < nsplit);
                        ov[r].x = ov[r].y = ov[r].z = ov[r].w = present ? 0u : 0xffffffffu;
                        mv[r].x = mv[r].y = present ? 0u : 0x007fffffu;
                        mv[r].z = mv[r].w = present ? 0u : 0xffffffffu;
                    }
                    float w0[PROUNDS], w1[PROUNDS];
                    bool wdone = false;
                    uint32_t spins = 0;
                    while (true) {
                        bool need_m = false, need_o = false;
#pragma unroll
                        for (int r = 0; r < PROUNDS; r++) {
                            const bool nm = min4(mv[r]) == 0u;
                            const bool no = min4(ov[r]) == 0u;
                            need_m |= nm;
                            need_o |= no;
                            ld_pred_v4(mv[r], pm + r * PPR * 2, nm);
                            ld_pred_v4(ov[r], po + r * PPR * 2, no);
                        }
                        const bool any_m = __any_sync(0xffffffffu, need_m);
                        const bool any_o = __any_sync(0xffffffffu, need_o);
                        if (!any_m && !wdone) {
                            float M0 = -INFINITY, M1 = -INFINITY;
#pragma unroll
                            for (int r = 0; r < PROUNDS; r++) {
                                M0 = fmaxf(M0, dec(mv[r].x));
                                M1 = fmaxf(M1, dec(mv[r].y));
                            }
                            M0 = warp_max_f32(M0);
                            M1 = warp_max_f32(M1);
                            if (M0 == -INFINITY) M0 = 0.f;
                            if (M1 == -INFINITY) M1 = 0.f;
                            float L0 = 0.f, L1 = 0.f;
#pragma unroll
                            for (int r = 0; r < PROUNDS; r++) {
                                w0[r] = ex2(dec(mv[r].x) - M0);
                                w1[r] = ex2(dec(mv[r].y) - M1);
                                L0 = fmaf(w0[r], dec(mv[r].z), L0);
                                L1 = fmaf(w1[r], dec(mv[r].w), L1);
                            }
#pragma unroll
                            for (int d = 2; d <= 16; d <<= 1) {
                                L0 += __shfl_xor_sync(0xffffffffu, L0, d);
                                L1 += __shfl_xor_sync(0xffffffffu, L1, d);
                            }
                            const float i0 = rcp_approx(L0), i1 = rcp_approx(L1);
#pragma unroll
                            for (int r = 0; r < PROUNDS; r++) { w0[r] *= i0; w1[r] *= i1; }
                            wdone = true;
                        }
                        if (!any_m && !any_o) break;
                        if (++spins > (1u << 22)) __trap();
                    }
                    float acc0 = 0.f, acc1 = 0.f, acc2 = 0.f, acc3 = 0.f;
#pragma unroll
                    for (int r = 0; r < PROUNDS; r++) {
                        acc0 = fmaf(w0[r], dec(ov[r].x), acc0);
                        acc1 = fmaf(w1[r], dec(ov[r].y), acc1);
                        acc2 = fmaf(w0[r], dec(ov[r].z), acc2);
                        acc3 = fmaf(w1[r], dec(ov[r].w), acc3);
                    }
#pragma unroll
                    for (int d = 2; d <= 16; d <<= 1) {
                        acc0 += __shfl_xor_sync(0xffffffffu, acc0, d);
                        acc1 += __shfl_xor_sync(0xffffffffu, acc1, d);
                        acc2 += __shfl_xor_sync(0xffffffffu, acc2, d);
                        acc3 += __shfl_xor_sync(0xffffffffu, acc3, d);
                    }
                    __nv_bfloat16* o0 = out + (size_t)(2 * j) * DH + mt * 16 + gq;
                    const bool pr = last && ii == 0;
                    st_pred_u16(o0, bf16_bits(acc0), pr);
                    st_pred_u16(o0 + DH, bf16_bits(acc1), pr);
                    st_pred_u16(o0 + 8, bf16_bits(acc2), pr);
                    st_pred_u16(o0 + DH + 8, bf16_bits(acc3), pr);
                    st_pred_zero_v2(&g_ticket[group * 32], last && ri == 0 && lane == 0);
                }
                if (last) break;
            }
            if (++st == NST) { st = 0; ph ^= 1; }
        }
        if (threadIdx.x == 32) DBG(5);
        return;
    }

    {
        if (lane < NST) sts_u32(sstat + 4u * lane, (uint32_t)e0);
        __syncwarp();
        if (lane != 0) return;

        uint64_t pol;
        asm volatile("createpolicy.fractional.L2::evict_first.b64 %0, 1.0;" : "=l"(pol));
        unsigned int* ticket = &g_ticket[group * 32];
        const int dyn_base = NST * nsplit;
        const int nstage_bt = min(nb, SBT_MAX) & ~3;
        const int lk = nb * BS;
        const int len = (ctx_raw <= 0) ? lk : min(ctx_raw, lk);
        const int nunits = (len + TOK - 1) / TOK;
        int st = 0;
        uint32_t ph = 1;
        int u = 0;
#pragma unroll 1
        for (;; u++) {
            mbar_wait(emptyK(st), ph);
            int uidx;
            if (u < NST) uidx = split + u * nsplit;
            else uidx = dyn_base + (int)atom_inc(ticket);
            if (uidx >= nunits) break;
            const int pidx = uidx / UPP;
            int page;
            if (u < NST) {
                page = (int)lds_u32(sstat + 4u * u);
            } else {
                if (u == NST && nstage_bt > 0) mbar_wait(btbar, 0);
                page = (pidx < nstage_bt) ? (int)lds_u32(sbt_base + pidx * 4) : __ldg(bt + pidx);
            }
            const int row = page * BS + (uidx % UPP) * TOK;
            const uint32_t kdst = sbase + st * 2 * TILE;
            sts_u32(slot(st), (uint32_t)uidx);
            mbar_expect_tx(fullK(st), TILE);
            tma_load_3d(kdst, &tmK, row, group * 2 * G, fullK(st), pol);
            mbar_wait(emptyV(st), ph);
            mbar_expect_tx(fullV(st), TILE);
            tma_load_3d(kdst + TILE, &tmV, row, group * 2 * G, fullV(st), pol);
            if (u == 0) {
                DBG(1);
                if (nstage_bt > 0) {
                    mbar_expect_tx(btbar, nstage_bt * 4);
                    bulk_g2s(sbt_base, bt, nstage_bt * 4, btbar);
                }
            }
            if (++st == NST) { st = 0; ph ^= 1; }
        }
        sts_u32(lastseq, (uint32_t)(u - 1));
        sts_u32(slot(st), INFO_EMPTY);
        mbar_arrive(fullK(st));
        if (u > 0 && u <= NST && nstage_bt > 0) mbar_wait(btbar, 0);
        mbar_arrive(rdybar);
        DBG(2);
    }
}

typedef CUresult (*EncodeTiledFn)(CUtensorMap*, CUtensorMapDataType, cuuint32_t, void*, const cuuint64_t*,
                                  const cuuint64_t*, const cuuint32_t*, const cuuint32_t*, CUtensorMapInterleave,
                                  CUtensorMapSwizzle, CUtensorMapL2promotion, CUtensorMapFloatOOBfill);

bool make_map(EncodeTiledFn enc_fn, CUtensorMap* tm, const void* base, uint64_t rows) {
    cuuint64_t gd[3] = {64, rows, 32};
    cuuint64_t gs[2] = {4096, 128};
    cuuint32_t bd[3] = {64, (cuuint32_t)TOK, (cuuint32_t)(2 * G)};
    cuuint32_t es[3] = {1, 1, 1};
    return enc_fn(tm, CU_TENSOR_MAP_DATA_TYPE_BFLOAT16, 3, const_cast<void*>(base), gd, gs, bd, es,
                  CU_TENSOR_MAP_INTERLEAVE_NONE, CU_TENSOR_MAP_SWIZZLE_128B, CU_TENSOR_MAP_L2_PROMOTION_L2_256B,
                  CU_TENSOR_MAP_FLOAT_OOB_FILL_NONE) == CUDA_SUCCESS;
}

}

extern "C" void kernel_launch(void* const* d_in, const int* in_sizes, int n_in, void* d_out, int out_size) {
    (void)n_in; (void)out_size;
    const __nv_bfloat16* q = (const __nv_bfloat16*)d_in[0];
    const void* kc = d_in[1];
    const void* vc = d_in[2];
    const int* bt = (const int*)d_in[3];
    const int* ctx = (const int*)d_in[4];
    __nv_bfloat16* out = (__nv_bfloat16*)d_out;

    static EncodeTiledFn enc_fn = nullptr;
    static int num_sms = 0;
    if (!enc_fn) {
        void* fn = nullptr;
        cudaDriverEntryPointQueryResult qr;
        cudaGetDriverEntryPoint("cuTensorMapEncodeTiled", &fn, cudaEnableDefault, &qr);
        enc_fn = (EncodeTiledFn)fn;
        int dev = 0;
        cudaGetDevice(&dev);
        cudaDeviceGetAttribute(&num_sms, cudaDevAttrMultiProcessorCount, dev);
        cudaFuncSetAttribute(paged_decode_kernel, cudaFuncAttributeMaxDynamicSharedMemorySize, SMEM_BYTES);
    }
    const uint64_t rows = (uint64_t)in_sizes[1] / (HKV * DH);
    const int nb = in_sizes[3];
    CUtensorMap tmK, tmV;
    make_map(enc_fn, &tmK, kc, rows);
    make_map(enc_fn, &tmV, vc, rows);
    int nsplit = num_sms / NGROUP;
    if (nsplit > MAX_SPLIT) nsplit = MAX_SPLIT;
    if (nsplit < 1) nsplit = 1;
    paged_decode_kernel<<<nsplit * NGROUP, NTHREADS, SMEM_BYTES, cudaStreamPerThread>>>(tmK, tmV, q, bt, ctx, out, nb, nsplit);
}
```

```cpp
#include <cuda_runtime.h>
#include <cuda_bf16.h>
#include <cuda.h>
#include <stdint.h>

namespace {

constexpr int HKV = 16;
constexpr int DH = 128;
constexpr int BS = 16;
constexpr int G = 8;
constexpr int TOK = 8;
constexpr int UPP = BS / TOK;
constexpr int NGROUP = HKV / G;
constexpr int NST = 3;
constexpr int CHUNK = TOK * 128;
constexpr int TILE = G * 2 * CHUNK;
constexpr int NCW = G;
constexpr int NTHREADS = (NCW + 2) * 32;
constexpr int MAX_SMS = 132;
constexpr int MAX_SPLIT = MAX_SMS / NGROUP;
constexpr int PPR = 16;
constexpr int PROUNDS = (MAX_SPLIT + PPR - 1) / PPR;
constexpr int PMAX = PROUNDS * PPR;
constexpr int NITEM = HKV * 8 * 4;
constexpr int NREADER = G * 8 * 4;
constexpr int RW = 4;
constexpr uint32_t INFO_EMPTY = 0x80000000u;
constexpr int SBT_MAX = 4096;
constexpr int SMEM_BYTES = NST * 2 * TILE + SBT_MAX * 4 + 1024 + 512;
constexpr int WARM_IT = 2;

__device__ uint4 g_scr_o[NITEM * PMAX * 2];
__device__ uint4 g_scr_ml[HKV * PMAX * 2];
__device__ unsigned int g_ticket[NGROUP * 32];

#define DBG(slot) do {} while (0)

__device__ __forceinline__ uint32_t smem_u32(const void* p) { return (uint32_t)__cvta_generic_to_shared(p); }

__device__ __forceinline__ void mbar_init(uint32_t bar, uint32_t cnt) {
    asm volatile("mbarrier.init.shared::cta.b64 [%0], %1;" ::"r"(bar), "r"(cnt) : "memory");
}
__device__ __forceinline__ void mbar_expect_tx(uint32_t bar, uint32_t bytes) {
    asm volatile("mbarrier.arrive.expect_tx.shared::cta.b64 _, [%0], %1;" ::"r"(bar), "r"(bytes) : "memory");
}
__device__ __forceinline__ void mbar_arrive(uint32_t bar) {
    asm volatile("mbarrier.arrive.shared::cta.b64 _, [%0];" ::"r"(bar) : "memory");
}
__device__ __forceinline__ bool mbar_try_wait(uint32_t bar, uint32_t parity) {
    uint32_t ok;
    asm volatile(
        "{\n.reg .pred p;\n"
        "mbarrier.try_wait.parity.shared::cta.b64 p, [%1], %2;\n"
        "selp.u32 %0, 1, 0, p;\n}\n"
        : "=r"(ok)
        : "r"(bar), "r"(parity)
        : "memory");
    return ok != 0;
}
__device__ __forceinline__ void mbar_wait(uint32_t bar, uint32_t parity) {
    uint32_t spins = 0;
    while (!mbar_try_wait(bar, parity)) {
        if (++spins > (1u << 22)) __trap();
    }
}
__device__ __forceinline__ void tma_load_3d(uint32_t dst, const CUtensorMap* tm, int row, int chunk, uint32_t bar, uint64_t pol) {
    asm volatile(
        "cp.async.bulk.tensor.3d.shared::cluster.global.mbarrier::complete_tx::bytes.L2::cache_hint "
        "[%0], [%1, {%3, %4, %5}], [%2], %6;"
        ::"r"(dst), "l"(tm), "r"(bar), "r"(0), "r"(row), "r"(chunk), "l"(pol)
        : "memory");
}
__device__ __forceinline__ void bulk_g2s(uint32_t dst, const void* src, uint32_t bytes, uint32_t bar) {
    asm volatile("cp.async.bulk.shared::cluster.global.mbarrier::complete_tx::bytes [%0], [%1], %2, [%3];"
                 ::"r"(dst), "l"(src), "r"(bytes), "r"(bar) : "memory");
}
__device__ __forceinline__ void sts_u32(uint32_t addr, uint32_t v) {
    asm volatile("st.shared.u32 [%0], %1;" ::"r"(addr), "r"(v) : "memory");
}
__device__ __forceinline__ uint32_t lds_u32(uint32_t addr) {
    uint32_t v;
    asm volatile("ld.shared.u32 %0, [%1];" : "=r"(v) : "r"(addr) : "memory");
    return v;
}
__device__ __forceinline__ void ldsm_x4(uint32_t& r0, uint32_t& r1, uint32_t& r2, uint32_t& r3, uint32_t addr) {
    asm volatile("ldmatrix.sync.aligned.m8n8.x4.shared.b16 {%0,%1,%2,%3}, [%4];"
                 : "=r"(r0), "=r"(r1), "=r"(r2), "=r"(r3) : "r"(addr) : "memory");
}
__device__ __forceinline__ void ldsm_x4_t(uint32_t& r0, uint32_t& r1, uint32_t& r2, uint32_t& r3, uint32_t addr) {
    asm volatile("ldmatrix.sync.aligned.m8n8.x4.trans.shared.b16 {%0,%1,%2,%3}, [%4];"
                 : "=r"(r0), "=r"(r1), "=r"(r2), "=r"(r3) : "r"(addr) : "memory");
}
__device__ __forceinline__ void mma_k16(float (&d)[4], uint32_t a0, uint32_t a1, uint32_t a2, uint32_t a3,
                                        uint32_t b0, uint32_t b1) {
    asm volatile(
        "mma.sync.aligned.m16n8k16.row.col.f32.bf16.bf16.f32 {%0,%1,%2,%3}, {%4,%5,%6,%7}, {%8,%9}, {%0,%1,%2,%3};"
        : "+f"(d[0]), "+f"(d[1]), "+f"(d[2]), "+f"(d[3])
        : "r"(a0), "r"(a1), "r"(a2), "r"(a3), "r"(b0), "r"(b1));
}
__device__ __forceinline__ void mma_k8(float (&d)[4], uint32_t a0, uint32_t a1, uint32_t b0) {
    asm volatile(
        "mma.sync.aligned.m16n8k8.row.col.f32.bf16.bf16.f32 {%0,%1,%2,%3}, {%4,%5}, {%6}, {%0,%1,%2,%3};"
        : "+f"(d[0]), "+f"(d[1]), "+f"(d[2]), "+f"(d[3])
        : "r"(a0), "r"(a1), "r"(b0));
}
__device__ __forceinline__ uint32_t pack_bf16(float lo, float hi) {
    uint32_t r;
    asm("cvt.rn.bf16x2.f32 %0, %1, %2;" : "=r"(r) : "f"(hi), "f"(lo));
    return r;
}
__device__ __forceinline__ float ex2(float x) {
    float y;
    asm("ex2.approx.ftz.f32 %0, %1;" : "=f"(y) : "f"(x));
    return y;
}
__device__ __forceinline__ float rcp_approx(float x) {
    float y;
    asm("rcp.approx.ftz.f32 %0, %1;" : "=f"(y) : "f"(x));
    return y;
}
__device__ __forceinline__ uint32_t enc(float x) { return max(~__float_as_uint(x), 1u); }
__device__ __forceinline__ float dec(uint32_t u) { return __uint_as_float(~u); }
__device__ __forceinline__ void st_zero_v4(uint4* p) {
    asm volatile("st.relaxed.gpu.global.v4.u32 [%0], {0, 0, 0, 0};" ::"l"(p) : "memory");
}
__device__ __forceinline__ void st_pred_v4(uint4* p, uint32_t a, uint32_t b, uint32_t c, uint32_t d, bool pred) {
    asm volatile("{\n.reg .pred p;\nsetp.ne.u32 p, %5, 0;\n@p st.relaxed.gpu.global.v4.u32 [%0], {%1,%2,%3,%4};\n}\n"
                 ::"l"(p), "r"(a), "r"(b), "r"(c), "r"(d), "r"((uint32_t)pred) : "memory");
}
__device__ __forceinline__ void ld_pred_v4(uint4& v, const uint4* p, bool pred) {
    asm volatile("{\n.reg .pred p;\nsetp.ne.u32 p, %5, 0;\n@p ld.relaxed.gpu.global.v4.u32 {%0,%1,%2,%3}, [%4];\n}\n"
                 : "+r"(v.x), "+r"(v.y), "+r"(v.z), "+r"(v.w) : "l"(p), "r"((uint32_t)pred) : "memory");
}
__device__ __forceinline__ void st_pred_u16(void* p, uint16_t v, bool pred) {
    asm volatile("{\n.reg .pred p;\nsetp.ne.u32 p, %2, 0;\n@p st.global.u16 [%0], %1;\n}\n"
                 ::"l"(p), "h"(v), "r"((uint32_t)pred) : "memory");
}
__device__ __forceinline__ void st_pred_zero_v2(void* p, bool pred) {
    asm volatile("{\n.reg .pred p;\nsetp.ne.u32 p, %1, 0;\n@p st.relaxed.gpu.global.v2.u32 [%0], {0, 0};\n}\n"
                 ::"l"(p), "r"((uint32_t)pred) : "memory");
}
__device__ __forceinline__ uint32_t atom_inc(unsigned int* p) {
    uint32_t v;
    asm volatile("{\n.reg .u32 t;\nmov.u32 t, %laneid;\nadd.u32 t, t, 1;\n"
                 "atom.relaxed.gpu.global.add.u32 %0, [%1], t;\n}\n" : "=r"(v) : "l"(p) : "memory");
    return v;
}
__device__ __forceinline__ uint32_t min4(const uint4& v) { return min(min(v.x, v.y), min(v.z, v.w)); }
__device__ __forceinline__ float warp_max_f32(float x) {
    int k = __float_as_int(x);
    k ^= (k >> 31) & 0x7fffffff;
    k = __reduce_max_sync(0xffffffffu, k);
    k ^= (k >> 31) & 0x7fffffff;
    return __int_as_float(k);
}
__device__ __forceinline__ uint16_t bf16_bits(float x) { return __bfloat16_as_ushort(__float2bfloat16(x)); }

__global__ void __launch_bounds__(NTHREADS, 1)
paged_decode_kernel(const __grid_constant__ CUtensorMap tmK, const __grid_constant__ CUtensorMap tmV,
                    const __nv_bfloat16* __restrict__ q, const int* __restrict__ bt,
                    const int* __restrict__ ctx, __nv_bfloat16* __restrict__ out, int nb, int nsplit) {
    extern __shared__ uint8_t smem_raw[];
    const uint32_t sbase = (smem_u32(smem_raw) + 1023u) & ~1023u;
    const uint32_t sbt_base = sbase + NST * 2 * TILE;
    const uint32_t bar_base = sbt_base + SBT_MAX * 4;
    auto fullK = [&](int s) { return bar_base + 8u * s; };
    auto fullV = [&](int s) { return bar_base + 8u * (NST + s); };
    auto emptyK = [&](int s) { return bar_base + 8u * (2 * NST + s); };
    auto emptyV = [&](int s) { return bar_base + 8u * (3 * NST + s); };
    const uint32_t btbar = bar_base + 8u * (4 * NST);
    const uint32_t rdybar = bar_base + 8u * (4 * NST + 1);
    auto slot = [&](int s) { return bar_base + 8u * (4 * NST + 2) + 4u * s; };
    const uint32_t sstat = bar_base + 8u * (4 * NST + 2) + 4u * NST;
    const uint32_t lastseq = sstat + 4u * NST;

    const int warp = threadIdx.x >> 5;
    const int lane = threadIdx.x & 31;
    const int group = blockIdx.x % NGROUP;
    const int split = blockIdx.x / NGROUP;

    if (threadIdx.x == 0) {
        asm volatile("prefetch.tensormap [%0];" ::"l"(&tmK) : "memory");
        asm volatile("prefetch.tensormap [%0];" ::"l"(&tmV) : "memory");
    }
    int e0 = 0, ctx_raw;
    {
        const int idx0 = (split + (int)threadIdx.x * nsplit) / UPP;
        const uint32_t pr = (threadIdx.x < NST && idx0 < nb) ? 1u : 0u;
        asm volatile("{\n.reg .pred p;\nsetp.ne.u32 p, %2, 0;\n@p ld.global.nc.u32 %0, [%1];\n}\n"
                     : "+r"(e0) : "l"(bt + (pr ? idx0 : 0)), "r"(pr));
        asm volatile("ld.global.nc.u32 %0, [%1];" : "=r"(ctx_raw) : "l"(ctx));
    }
    if (threadIdx.x == 0) {
#pragma unroll
        for (int s = 0; s < NST; s++) {
            mbar_init(fullK(s), 1);
            mbar_init(fullV(s), 1);
            mbar_init(emptyK(s), NCW);
            mbar_init(emptyV(s), NCW);
        }
        mbar_init(btbar, 1);
        mbar_init(rdybar, 2);
        sts_u32(lastseq, 0xffffffffu);
        asm volatile("fence.mbarrier_init.release.cluster;" ::: "memory");
        asm volatile("fence.proxy.async.shared::cta;" ::: "memory");
    }
    if (warp == 0) {
        __syncwarp();
        asm volatile("bar.arrive 1, %0;" ::"n"(NTHREADS) : "memory");
    }

    if (warp == NCW + 1) {
        asm volatile("bar.sync 1, %0;" ::"n"(NTHREADS) : "memory");
        uint4* po = &g_scr_o[((group * NREADER + (lane >> 1)) * PMAX + split) * 2 + (lane & 1)];
#pragma unroll
        for (int k = 0; k < NREADER / 16; k++) st_zero_v4(po + k * 16 * PMAX * 2);
        if (lane < 2 * G) st_zero_v4(&g_scr_ml[((group * G + (lane >> 1)) * PMAX + split) * 2 + (lane & 1)]);
        __threadfence();
        __syncwarp();
        if (lane == 0) {
            unsigned int* ready = &g_ticket[group * 32 + 1];
            asm volatile("red.relaxed.gpu.global.add.u32 [%0], 1;" ::"l"(ready) : "memory");
            uint32_t spins = 0;
            while (true) {
                unsigned int v;
                asm volatile("ld.acquire.gpu.global.u32 %0, [%1];" : "=r"(v) : "l"(ready) : "memory");
                if (v >= (unsigned int)nsplit) break;
                if (++spins > (1u << 21)) __trap();
                __nanosleep(500);
            }
            mbar_arrive(rdybar);
            DBG(7);
        }
        return;
    }

    if (warp != 0) {
        const int cw = warp - 1;
        const int g = lane >> 2;
        const int t = lane & 3;
        const int kvh = group * G + cw;

        uint32_t qa[8][2];
        {
            const uint32_t* qp = reinterpret_cast<const uint32_t*>(q + (size_t)(kvh * 2 + (g & 1)) * DH);
#pragma unroll
            for (int ks = 0; ks < 8; ks++) {
                uint32_t v0 = __ldg(qp + ks * 8 + t);
                uint32_t v1 = __ldg(qp + ks * 8 + 4 + t);
                qa[ks][0] = (g < 2) ? v0 : 0u;
                qa[ks][1] = (g < 2) ? v1 : 0u;
            }
        }
        asm volatile("bar.sync 1, %0;" ::"n"(NTHREADS) : "memory");

        const int lk = nb * BS;
        const bool uniform = (ctx_raw <= 0);
        const int len = uniform ? lk : min(ctx_raw, lk);
        const float cscale = 0.08838834764831845f * 1.4426950408889634f;

        float o[8][4];
#pragma unroll
        for (int i = 0; i < 8; i++) { o[i][0] = o[i][1] = o[i][2] = o[i][3] = 0.f; }
        float m_run = -INFINITY;
        float l_run = 0.f;

        const int r8 = lane & 7;
        const int mi = lane >> 3;
        const uint32_t lane_off = (uint32_t)(cw * 2 * CHUNK + r8 * 128);

        int st = 0;
        uint32_t ph = 0;
#pragma unroll 1
        for (int it = 0;; it++) {
            const uint32_t kb = sbase + st * 2 * TILE + lane_off;
            const uint32_t vb = kb + TILE;
            mbar_wait(fullK(st), ph);
            const uint32_t info = lds_u32(slot(st));
            const bool empty = (info & INFO_EMPTY) != 0;
            const bool last = empty || lds_u32(lastseq) == (uint32_t)it;
            const bool epi = last || it == WARM_IT;
            uint32_t pb = 0;
            if (!empty) {
                float s0[4] = {0.f, 0.f, 0.f, 0.f}, s1[4] = {0.f, 0.f, 0.f, 0.f};
#pragma unroll
                for (int c = 0; c < 2; c++) {
#pragma unroll
                    for (int hf = 0; hf < 2; hf++) {
                        uint32_t b0, b1, b2, b3;
                        ldsm_x4(b0, b1, b2, b3, kb + c * CHUNK + (uint32_t)(((hf * 4 + mi) ^ r8) << 4));
                        const int ks = c * 4 + hf * 2;
                        if (c == 0) {
                            mma_k16(s0, qa[ks][0], 0u, qa[ks][1], 0u, b0, b1);
                            mma_k16(s0, qa[ks + 1][0], 0u, qa[ks + 1][1], 0u, b2, b3);
                        } else {
                            mma_k16(s1, qa[ks][0], 0u, qa[ks][1], 0u, b0, b1);
                            mma_k16(s1, qa[ks + 1][0], 0u, qa[ks + 1][1], 0u, b2, b3);
                        }
                    }
                }
                __syncwarp();
                if (lane == 0) mbar_arrive(emptyK(st));

                float sv0 = s0[0] + s1[0];
                float sv1 = s0[1] + s1[1];
                const int tok0 = (int)info * TOK;
                if (uniform) { sv0 = 0.f; sv1 = 0.f; }
                if (tok0 + TOK > len) {
                    const int tb = tok0 + 2 * t;
                    if (tb >= len) sv0 = -INFINITY;
                    if (tb + 1 >= len) sv1 = -INFINITY;
                }
                float mx = fmaxf(sv0, sv1);
                mx = fmaxf(mx, __shfl_xor_sync(0xffffffffu, mx, 1));
                mx = fmaxf(mx, __shfl_xor_sync(0xffffffffu, mx, 2));
                const float m_new = fmaxf(m_run, mx);
                const float m_use = (m_new == -INFINITY) ? 0.f : m_new;
                const float alpha = ex2((m_run - m_use) * cscale);
                const float mc = m_use * cscale;
                const float p0 = ex2(fmaf(sv0, cscale, -mc));
                const float p1 = ex2(fmaf(sv1, cscale, -mc));
                m_run = m_new;
                l_run = fmaf(l_run, alpha, p0 + p1);
                pb = pack_bf16(p0, p1);
                const float a0 = __shfl_sync(0xffffffffu, alpha, 0);
                const float a1 = __shfl_sync(0xffffffffu, alpha, 4);
                if (a0 != 1.f || a1 != 1.f) {
#pragma unroll
                    for (int i = 0; i < 8; i++) {
                        o[i][0] *= a0; o[i][1] *= a1; o[i][2] *= a0; o[i][3] *= a1;
                    }
                }
            }
            if (epi) {
                if (last) mbar_wait(rdybar, 0);
                float l = l_run;
                l += __shfl_xor_sync(0xffffffffu, l, 1);
                l += __shfl_xor_sync(0xffffffffu, l, 2);
                const float mc = m_run * cscale;
                const float m0 = __shfl_sync(0xffffffffu, mc, 0);
                const float m1 = __shfl_sync(0xffffffffu, mc, 4);
                const float l0 = __shfl_sync(0xffffffffu, l, 0);
                const float l1 = __shfl_sync(0xffffffffu, l, 4);
                st_pred_v4(&g_scr_ml[(kvh * PMAX + split) * 2 + (lane & 1)], enc(m0), enc(m1), enc(l0), enc(l1),
                           last && lane < 2);
            }
            if (!empty) {
                mbar_wait(fullV(st), ph);
#pragma unroll
                for (int mp = 0; mp < 4; mp++) {
                    uint32_t a0r, a1r, a2r, a3r;
                    ldsm_x4_t(a0r, a1r, a2r, a3r, vb + (mp >> 1) * CHUNK + (uint32_t)((((mp & 1) * 4 + mi) ^ r8) << 4));
                    mma_k8(o[2 * mp], a0r, a1r, pb);
                    mma_k8(o[2 * mp + 1], a2r, a3r, pb);
                }
                __syncwarp();
                if (lane == 0) mbar_arrive(emptyV(st));
            }
            if (epi) {
                {
                    uint4* po = &g_scr_o[((kvh * 32 + (g >> 1)) * PMAX + split) * 2 + (g & 1)];
                    const bool pr = last && t == 0;
#pragma unroll
                    for (int mt = 0; mt < 8; mt++) {
                        st_pred_v4(po + mt * 4 * PMAX * 2, enc(o[mt][0]), enc(o[mt][1]), enc(o[mt][2]), enc(o[mt][3]), pr);
                    }
                }
#pragma unroll 1
                for (int ri = (cw < RW) ? split * RW + cw : NREADER; ri < NREADER; ri += nsplit * RW) {
                    const int ii = lane >> 1;
                    const int gg = lane & 1;
                    const int j = group * G + (ri >> 5);
                    const int mt = (ri >> 2) & 7;
                    const int gq = (ri & 3) * 2 + gg;
                    const uint4* po = &g_scr_o[((group * NREADER + ri) * PMAX + ii) * 2 + gg];
                    const uint4* pm = &g_scr_ml[(j * PMAX + ii) * 2];
                    uint4 ov[PROUNDS], mv[PROUNDS];
#pragma unroll
                    for (int r = 0; r < PROUNDS; r++) {
                        const bool present = last && (r * PPR + ii < nsplit);
                        ov[r].x = ov[r].y = ov[r].z = ov[r].w = present ? 0u : 0xffffffffu;
                        mv[r].x = mv[r].y = present ? 0u : 0x007fffffu;
                        mv[r].z = mv[r].w = present ? 0u : 0xffffffffu;
                    }
                    uint32_t spins = 0;
                    while (true) {
                        bool anyneed = false;
#pragma unroll
                        for (int r = 0; r < PROUNDS; r++) {
                            const bool need = min(min4(ov[r]), min4(mv[r])) == 0u;
                            anyneed |= need;
                            ld_pred_v4(ov[r], po + r * PPR * 2, need);
                            ld_pred_v4(mv[r], pm + r * PPR * 2, need);
                        }
                        if (!__any_sync(0xffffffffu, anyneed)) break;
                        if (++spins > (1u << 22)) __trap();
                    }
                    float M0 = -INFINITY, M1 = -INFINITY;
#pragma unroll
                    for (int r = 0; r < PROUNDS; r++) {
                        M0 = fmaxf(M0, dec(mv[r].x));
                        M1 = fmaxf(M1, dec(mv[r].y));
                    }
                    M0 = warp_max_f32(M0);
                    M1 = warp_max_f32(M1);
                    if (M0 == -INFINITY) M0 = 0.f;
                    if (M1 == -INFINITY) M1 = 0.f;
                    float L0 = 0.f, L1 = 0.f, acc0 = 0.f, acc1 = 0.f, acc2 = 0.f, acc3 = 0.f;
#pragma unroll
                    for (int r = 0; r < PROUNDS; r++) {
                        const float w0 = ex2(dec(mv[r].x) - M0);
                        const float w1 = ex2(dec(mv[r].y) - M1);
                        L0 = fmaf(w0, dec(mv[r].z), L0);
                        L1 = fmaf(w1, dec(mv[r].w), L1);
                        acc0 = fmaf(w0, dec(ov[r].x), acc0);
                        acc1 = fmaf(w1, dec(ov[r].y), acc1);
                        acc2 = fmaf(w0, dec(ov[r].z), acc2);
                        acc3 = fmaf(w1, dec(ov[r].w), acc3);
                    }
#pragma unroll
                    for (int d = 2; d <= 16; d <<= 1) {
                        L0 += __shfl_xor_sync(0xffffffffu, L0, d);
                        L1 += __shfl_xor_sync(0xffffffffu, L1, d);
                        acc0 += __shfl_xor_sync(0xffffffffu, acc0, d);
                        acc1 += __shfl_xor_sync(0xffffffffu, acc1, d);
                        acc2 += __shfl_xor_sync(0xffffffffu, acc2, d);
                        acc3 += __shfl_xor_sync(0xffffffffu, acc3, d);
                    }
                    const float i0 = rcp_approx(L0), i1 = rcp_approx(L1);
                    __nv_bfloat16* o0 = out + (size_t)(2 * j) * DH + mt * 16 + gq;
                    const bool pr = last && ii == 0;
                    st_pred_u16(o0, bf16_bits(acc0 * i0), pr);
                    st_pred_u16(o0 + DH, bf16_bits(acc1 * i1), pr);
                    st_pred_u16(o0 + 8, bf16_bits(acc2 * i0), pr);
                    st_pred_u16(o0 + DH + 8, bf16_bits(acc3 * i1), pr);
                    st_pred_zero_v2(&g_ticket[group * 32], last && ri == 0 && lane == 0);
                }
                if (last) break;
            }
            if (++st == NST) { st = 0; ph ^= 1; }
        }
        if (threadIdx.x == 32) DBG(5);
        return;
    }

    {
        if (lane < NST) sts_u32(sstat + 4u * lane, (uint32_t)e0);
        __syncwarp();
        if (lane != 0) return;

        uint64_t pol;
        asm volatile("createpolicy.fractional.L2::evict_first.b64 %0, 1.0;" : "=l"(pol));
        unsigned int* ticket = &g_ticket[group * 32];
        const int dyn_base = NST * nsplit;
        const int nstage_bt = min(nb, SBT_MAX) & ~3;
        const int lk = nb * BS;
        const int len = (ctx_raw <= 0) ? lk : min(ctx_raw, lk);
        const int nunits = (len + TOK - 1) / TOK;
        int st = 0;
        uint32_t ph = 1;
        int u = 0;
#pragma unroll 1
        for (;; u++) {
            mbar_wait(emptyK(st), ph);
            int uidx;
            if (u < NST) uidx = split + u * nsplit;
            else uidx = dyn_base + (int)atom_inc(ticket);
            if (uidx >= nunits) break;
            const int pidx = uidx / UPP;
            int page;
            if (u < NST) {
                page = (int)lds_u32(sstat + 4u * u);
            } else {
                if (u == NST && nstage_bt > 0) mbar_wait(btbar, 0);
                page = (pidx < nstage_bt) ? (int)lds_u32(sbt_base + pidx * 4) : __ldg(bt + pidx);
            }
            const int row = page * BS + (uidx % UPP) * TOK;
            const uint32_t kdst = sbase + st * 2 * TILE;
            sts_u32(slot(st), (uint32_t)uidx);
            mbar_expect_tx(fullK(st), TILE);
            tma_load_3d(kdst, &tmK, row, group * 2 * G, fullK(st), pol);
            mbar_wait(emptyV(st), ph);
            mbar_expect_tx(fullV(st), TILE);
            tma_load_3d(kdst + TILE, &tmV, row, group * 2 * G, fullV(st), pol);
            if (u == 0) {
                DBG(1);
                if (nstage_bt > 0) {
                    mbar_expect_tx(btbar, nstage_bt * 4);
                    bulk_g2s(sbt_base, bt, nstage_bt * 4, btbar);
                }
            }
            if (++st == NST) { st = 0; ph ^= 1; }
        }
        sts_u32(lastseq, (uint32_t)(u - 1));
        sts_u32(slot(st), INFO_EMPTY);
        mbar_arrive(fullK(st));
        if (u > 0 && u <= NST && nstage_bt > 0) mbar_wait(btbar, 0);
        mbar_arrive(rdybar);
        DBG(2);
    }
}

typedef CUresult (*EncodeTiledFn)(CUtensorMap*, CUtensorMapDataType, cuuint32_t, void*, const cuuint64_t*,
                                  const cuuint64_t*, const cuuint32_t*, const cuuint32_t*, CUtensorMapInterleave,
                                  CUtensorMapSwizzle, CUtensorMapL2promotion, CUtensorMapFloatOOBfill);

bool make_map(EncodeTiledFn enc_fn, CUtensorMap* tm, const void* base, uint64_t rows) {
    cuuint64_t gd[3] = {64, rows, 32};
    cuuint64_t gs[2] = {4096, 128};
    cuuint32_t bd[3] = {64, (cuuint32_t)TOK, (cuuint32_t)(2 * G)};
    cuuint32_t es[3] = {1, 1, 1};
    return enc_fn(tm, CU_TENSOR_MAP_DATA_TYPE_BFLOAT16, 3, const_cast<void*>(base), gd, gs, bd, es,
                  CU_TENSOR_MAP_INTERLEAVE_NONE, CU_TENSOR_MAP_SWIZZLE_128B, CU_TENSOR_MAP_L2_PROMOTION_L2_256B,
                  CU_TENSOR_MAP_FLOAT_OOB_FILL_NONE) == CUDA_SUCCESS;
}

}

extern "C" void kernel_launch(void* const* d_in, const int* in_sizes, int n_in, void* d_out, int out_size) {
    (void)n_in; (void)out_size;
    const __nv_bfloat16* q = (const __nv_bfloat16*)d_in[0];
    const void* kc = d_in[1];
    const void* vc = d_in[2];
    const int* bt = (const int*)d_in[3];
    const int* ctx = (const int*)d_in[4];
    __nv_bfloat16* out = (__nv_bfloat16*)d_out;

    static EncodeTiledFn enc_fn = nullptr;
    static int num_sms = 0;
    if (!enc_fn) {
        void* fn = nullptr;
        cudaDriverEntryPointQueryResult qr;
        cudaGetDriverEntryPoint("cuTensorMapEncodeTiled", &fn, cudaEnableDefault, &qr);
        enc_fn = (EncodeTiledFn)fn;
        int dev = 0;
        cudaGetDevice(&dev);
        cudaDeviceGetAttribute(&num_sms, cudaDevAttrMultiProcessorCount, dev);
        cudaFuncSetAttribute(paged_decode_kernel, cudaFuncAttributeMaxDynamicSharedMemorySize, SMEM_BYTES);
    }
    const uint64_t rows = (uint64_t)in_sizes[1] / (HKV * DH);
    const int nb = in_sizes[3];
    CUtensorMap tmK, tmV;
    make_map(enc_fn, &tmK, kc, rows);
    make_map(enc_fn, &tmV, vc, rows);
    int nsplit = num_sms / NGROUP;
    if (nsplit > MAX_SPLIT) nsplit = MAX_SPLIT;
    if (nsplit < 1) nsplit = 1;
    paged_decode_kernel<<<nsplit * NGROUP, NTHREADS, SMEM_BYTES, cudaStreamPerThread>>>(tmK, tmV, q, bt, ctx, out, nb, nsplit);
}
```
